```python
import torch

def _softmax(x, axis=-1):
    return torch.softmax(x, dim=axis)
def _gelu(x):
    return torch.nn.functional.gelu(x, approximate="tanh")
def _silu(x):
    return torch.nn.functional.silu(x)
def _sigmoid(x):
    return torch.sigmoid(x)
def _layernorm(x, axis=-1, eps=1e-5):
    m = x.mean(dim=axis, keepdim=True)
    v = x.var(dim=axis, keepdim=True, unbiased=False)
    return (x - m) / torch.sqrt(v + eps)
def _scatter_add(tgt, idx, src, axis=0):
    return tgt.clone().index_add_(axis, idx, src)
def _segment_sum(src, seg, n):
    out = torch.zeros((n,) + src.shape[1:], dtype=src.dtype)
    return out.index_add_(0, seg, src)
def _pad(x, pw):
    flat = tuple(v for pair in reversed(pw) for v in pair)
    return torch.nn.functional.pad(x, flat)

kernel_name = 'standalone__deformable_dcnv1__vision'

def setup_inputs():

    _w = (lambda a: (lambda t: t.to(torch.bfloat16) if t.is_floating_point() else t)(torch.as_tensor(a)))
    H = W = 224
    C = 96
    K = 3
    return {
        "x": _w((lambda *s: torch.randn(*s, dtype=torch.bfloat16) * 0.05)(1, H, W, C)),
        "offset": _w((lambda *s: torch.randn(*s, dtype=torch.bfloat16) * 0.05)(1, H, W, 2 * K * K) * 0.5),
        "w": _w((lambda *s: torch.randn(*s, dtype=torch.bfloat16) * 0.05)(K, K, C, C) * (K * K * C) ** -0.5),
    }

def reference(x, offset, w):
    B, H, W, C = x.shape
    K = 3
    hh = (lambda x, dt: x.to(dt))(torch.arange(H), x.dtype).reshape(1, H, 1)
    ww = (lambda x, dt: x.to(dt))(torch.arange(W), x.dtype).reshape(1, 1, W)
    xf = x.reshape(B, H * W, C)
    def _gather(yi, xi):
        lin = (yi * W + xi).reshape(B, H * W)
        idx = (lambda x, n, axis: torch.repeat_interleave(x, n, dim=axis))(lin[..., None], C, axis=-1)
        return (lambda x, i, axis: torch.take_along_dim(x, i, dim=axis))(xf, idx, axis=1).reshape(B, H, W, C)
    taps = []
    for ki in range(K):
        for kj in range(K):
            t = ki * K + kj
            dy = offset[..., 2 * t]
            dx = offset[..., 2 * t + 1]
            py = torch.clip(hh + (ki - 0.5 * (K - 1)) + dy, 0.0, H - 1.0)
            px = torch.clip(ww + (kj - 0.5 * (K - 1)) + dx, 0.0, W - 1.0)
            y0 = torch.floor(py)
            x0 = torch.floor(px)
            y1 = torch.clip(y0 + 1.0, 0.0, H - 1.0)
            x1 = torch.clip(x0 + 1.0, 0.0, W - 1.0)
            wy = (py - y0)[..., None]
            wx = (px - x0)[..., None]
            y0i = (lambda x, dt: x.to(dt))(y0, torch.int64)
            y1i = (lambda x, dt: x.to(dt))(y1, torch.int64)
            x0i = (lambda x, dt: x.to(dt))(x0, torch.int64)
            x1i = (lambda x, dt: x.to(dt))(x1, torch.int64)
            v = (1 - wy) * (1 - wx) * _gather(y0i, x0i) + (1 - wy) * wx * _gather(y0i, x1i) + wy * (1 - wx) * _gather(y1i, x0i) + wy * wx * _gather(y1i, x1i)
            taps.append(v)
    samp = torch.stack(taps, 3)
    return torch.einsum("bhwkc,kco->bhwo", samp, w.reshape(K * K, C, C))
```

```cpp
#include <cuda_runtime.h>
#include <cuda.h>
#include <cuda_bf16.h>
#include <stdint.h>

namespace {

constexpr int IH = 224, IW = 224, IC = 96;
constexpr int GRID = 132, NTHREADS = 512;
constexpr int NI = 60, NR = GRID - NI;
constexpr int SLOT = 9216;
constexpr int SMEM_BYTES = 232448;
constexpr int PLANE = 66 * 64, UNIT = 6 * PLANE;
constexpr int SM_V = 256, SM_X = 8704, SM_W = 36 * PLANE + 512, SM_BAR = SM_W + 8 * SLOT;
constexpr int B_WF = 0, B_WE = 36, B_XF = 60, B_XR = 66, B_ST = 72, B_UR = 80, B_OF = 84, B_OS = 85, B_EP = 86, B_OK = 87, B_G = 88;
constexpr int O_CNT = 832, O_VER = 848, O_EPO = 852, O_LST = 864, O_COR = 1024;
constexpr int MAXEX = 16, QUEUE = 192;
constexpr uint32_t FAILED = 255;
constexpr int GSLICE = 144 * 64, SM_GX = 18 * SLOT;
constexpr int SM_RAW = SM_V + 3 * UNIT, SM_OFF = SM_X + SLOT;
constexpr int YSLICE = 36 * 10 * 64, SM_YX = 16 * SLOT, SM_YT = SM_YX + 3 * YSLICE;
#define PSLEEP 20
#define REDSEM "red.release"
#define XN 4
#define XJ4 3
#define XJ5 7
#define HAND 12
#define PUB1 10
#define TGRP 8
#define TDEP 0
#define TSBON 0
#define YPRMT 1
#define STW 0
#define LATE4 0
#define PW -1
#define TX 0
#define SPACE 2
#define VC 2
#define VGATE 0
#define YLAG 0
#define KEEP 0
#define YP1 3
#define YP2 6
#define MIX 1
#define YORD 1
#define Y0M 0
#define POLLT 3800
#define TS2 1
#define T2N 2
#define PUB0 3
#define GDT 3000
#define SCANB 3
#define XT1 1500
#define XT2 3800
#define XDT 500
#define YX0 900
#define YX1 5000
#define YX2 8500
#define YWT 2500
#define YWDT 1100

struct Scratch {
  uint4 u[16 * SLOT / 16];
  uint4 w[18 * SLOT / 16];
  uint32_t ready[32];
  uint2 req[QUEUE];
  uint2 res[QUEUE][48];
  uint2 mail[GRID][32];
};
__device__ __align__(128) Scratch g_scratch;

#define TSE(i)
#define TSB(i)

__device__ __forceinline__ float bf16lo(uint32_t v) { return __uint_as_float(v << 16); }
__device__ __forceinline__ float bf16hi(uint32_t v) { return __uint_as_float(v & 0xffff0000u); }
__device__ __forceinline__ uint32_t smem_u32(const void* p) { return (uint32_t)__cvta_generic_to_shared(p); }
__device__ __forceinline__ void mbar_init(uint32_t bar, uint32_t count) {
  asm volatile("mbarrier.init.shared::cta.b64 [%0], %1;\n" ::"r"(bar), "r"(count) : "memory");
}
__device__ __forceinline__ void mbar_expect_tx(uint32_t bar, uint32_t bytes) {
  asm volatile("mbarrier.arrive.expect_tx.shared::cta.b64 _, [%0], %1;\n" ::"r"(bar), "r"(bytes) : "memory");
}
__device__ __forceinline__ void mbar_wait(uint32_t bar, uint32_t parity = 0) {
  uint32_t done;
#pragma unroll 1
  for (uint32_t spin = 0; spin < (1u << 22); spin++) {
    asm volatile(
        "{\n.reg .pred p;\n"
        "mbarrier.try_wait.parity.shared::cta.b64 p, [%1], %2;\n"
        "selp.u32 %0, 1, 0, p;\n}\n"
        : "=r"(done)
        : "r"(bar), "r"(parity)
        : "memory");
    if (done) return;
  }
  __trap();
}
__device__ __forceinline__ uint32_t mbar_test(uint32_t bar, uint32_t parity = 0) {
  uint32_t done;
  asm volatile(
      "{\n.reg .pred p;\n"
      "mbarrier.test_wait.parity.shared::cta.b64 p, [%1], %2;\n"
      "selp.u32 %0, 1, 0, p;\n}\n"
      : "=r"(done)
      : "r"(bar), "r"(parity)
      : "memory");
  return done;
}
__device__ __forceinline__ uint32_t clock32() {
  uint32_t c;
  asm volatile("mov.u32 %0, %%clock;\n" : "=r"(c)::"memory");
  return c;
}
__device__ __forceinline__ void wait_until(uint32_t t0, uint32_t dt) {
  while (clock32() - t0 < dt) __nanosleep(50);
}
__device__ __forceinline__ void mbar_wait_cluster(uint32_t bar, uint32_t parity = 0) {
  uint32_t done;
#pragma unroll 1
  for (uint32_t spin = 0; spin < (1u << 22); spin++) {
    asm volatile(
        "{\n.reg .pred p;\n"
        "mbarrier.try_wait.parity.acquire.cluster.shared::cta.b64 p, [%1], %2;\n"
        "selp.u32 %0, 1, 0, p;\n}\n"
        : "=r"(done)
        : "r"(bar), "r"(parity)
        : "memory");
    if (done) return;
  }
  __trap();
}
__device__ __forceinline__ void tma_load_3d(uint32_t dst, const CUtensorMap* tm, uint32_t bar, int c0, int c1, int c2) {
  asm volatile(
      "cp.async.bulk.tensor.3d.shared::cluster.global.mbarrier::complete_tx::bytes [%0], [%1, {%3, %4, %5}], [%2];\n" ::"r"(dst),
      "l"(reinterpret_cast<uint64_t>(tm)), "r"(bar), "r"(c0), "r"(c1), "r"(c2)
      : "memory");
}
__device__ __forceinline__ void tma_load_5d(uint32_t dst, const CUtensorMap* tm, uint32_t bar, int c, int kj, int ki) {
  asm volatile(
      "cp.async.bulk.tensor.5d.shared::cluster.global.mbarrier::complete_tx::bytes [%0], [%1, {%3, %4, %3, %5, %6}], [%2];\n" ::"r"(dst),
      "l"(reinterpret_cast<uint64_t>(tm)), "r"(bar), "r"(0), "r"(c), "r"(kj), "r"(ki)
      : "memory");
}
__device__ __forceinline__ void tma_load_4d(uint32_t dst, const CUtensorMap* tm, uint32_t bar, int c1, int c2, int c3) {
  asm volatile(
      "cp.async.bulk.tensor.4d.shared::cluster.global.mbarrier::complete_tx::bytes [%0], [%1, {%3, %4, %5, %6}], [%2];\n" ::"r"(dst),
      "l"(reinterpret_cast<uint64_t>(tm)), "r"(bar), "r"(0), "r"(c1), "r"(c2), "r"(c3)
      : "memory");
}
__device__ __forceinline__ void tma_load_5t(uint32_t dst, const CUtensorMap* tm, uint32_t bar, int kj, int chunk) {
  asm volatile(
      "cp.async.bulk.tensor.5d.shared::cluster.global.mbarrier::complete_tx::bytes [%0], [%1, {%3, %3, %4, %3, %5}], [%2];\n" ::"r"(dst),
      "l"(reinterpret_cast<uint64_t>(tm)), "r"(bar), "r"(0), "r"(kj), "r"(chunk)
      : "memory");
}
template <int BYTES>
__device__ __forceinline__ void bulk_load(uint32_t dst, const void* src, uint32_t bar) {
  asm volatile("cp.async.bulk.shared::cluster.global.mbarrier::complete_tx::bytes [%0], [%1], %3, [%2];\n" ::"r"(dst), "l"(src),
               "r"(bar), "n"(BYTES)
               : "memory");
}
template <int BYTES>
__device__ __forceinline__ void bulk_store(void* dst, uint32_t src) {
  asm volatile("cp.async.bulk.global.shared::cta.bulk_group [%0], [%1], %2;\n" ::"l"(dst), "r"(src), "n"(BYTES) : "memory");
}
__device__ __forceinline__ void tma_store3(const CUtensorMap* tm, uint32_t src, int c0, int c1, int c2) {
  asm volatile("cp.async.bulk.tensor.3d.global.shared::cta.bulk_group [%0, {%2, %3, %4}], [%1];\n" ::"l"(
                   reinterpret_cast<uint64_t>(tm)),
               "r"(src), "r"(c0), "r"(c1), "r"(c2)
               : "memory");
}
__device__ __forceinline__ void tma_store(const CUtensorMap* tm, uint32_t src, int c1, int c2) {
  asm volatile("cp.async.bulk.tensor.4d.global.shared::cta.bulk_group [%0, {%2, %3, %4, %2}], [%1];\n" ::"l"(
                   reinterpret_cast<uint64_t>(tm)),
               "r"(src), "r"(0), "r"(c1), "r"(c2)
               : "memory");
}
__device__ __forceinline__ uint64_t w_desc(uint32_t saddr) {
  return (uint64_t)((saddr & 0x3FFFF) >> 4) | ((uint64_t)(1024 >> 4) << 16) | ((uint64_t)(512 >> 4) << 32) | ((uint64_t)2 << 62);
}
__device__ __forceinline__ uint64_t a_desc(uint32_t saddr) {
  return (uint64_t)((saddr & 0x3FFFF) >> 4) | ((uint64_t)1 << 16) | ((uint64_t)(512 >> 4) << 32) | ((uint64_t)2 << 62);
}
#define ACC_OPERANDS(c, d)                                                                                        \
  c(d[0]), c(d[1]), c(d[2]), c(d[3]), c(d[4]), c(d[5]), c(d[6]), c(d[7]), c(d[8]),      \
      c(d[9]), c(d[10]), c(d[11]), c(d[12]), c(d[13]), c(d[14]), c(d[15]), c(d[16]),       \
      c(d[17]), c(d[18]), c(d[19]), c(d[20]), c(d[21]), c(d[22]), c(d[23]), c(d[24]),      \
      c(d[25]), c(d[26]), c(d[27]), c(d[28]), c(d[29]), c(d[30]), c(d[31]), c(d[32]),      \
      c(d[33]), c(d[34]), c(d[35]), c(d[36]), c(d[37]), c(d[38]), c(d[39]), c(d[40]),      \
      c(d[41]), c(d[42]), c(d[43]), c(d[44]), c(d[45]), c(d[46]), c(d[47])
#define ACC_LIST                                                                   \
  "{%0, %1, %2, %3, %4, %5, %6, %7, %8, %9, %10, %11, %12, %13, %14, %15, "        \
  "%16, %17, %18, %19, %20, %21, %22, %23, %24, %25, %26, %27, %28, %29, %30, %31, " \
  "%32, %33, %34, %35, %36, %37, %38, %39, %40, %41, %42, %43, %44, %45, %46, %47}, "
__device__ __forceinline__ void wgmma_ss(float* d, uint64_t adesc, uint64_t bdesc, int accumulate = 1) {
  asm volatile(
      "{\n.reg .pred p;\nsetp.ne.b32 p, %50, 0;\n"
      "wgmma.mma_async.sync.aligned.m64n96k16.f32.bf16.bf16 " ACC_LIST "%48, %49, p, 1, 1, 0, 1;\n}\n"
      : ACC_OPERANDS("+f", d)
      : "l"(adesc), "l"(bdesc), "r"(accumulate));
}
__device__ __forceinline__ void wgmma_fence() { asm volatile("wgmma.fence.sync.aligned;\n" ::: "memory"); }
__device__ __forceinline__ void wgmma_commit() { asm volatile("wgmma.commit_group.sync.aligned;\n" ::: "memory"); }
template <int N>
__device__ __forceinline__ void wgmma_wait() { asm volatile("wgmma.wait_group.sync.aligned %0;\n" ::"n"(N) : "memory"); }
__device__ __forceinline__ void acc_fence(float* d) {
#pragma unroll
  for (int i = 0; i < 48; i++) asm volatile("" : "+f"(d[i])::"memory");
}
__device__ __forceinline__ void arrive_if(uint32_t bar) {
  asm volatile("{\n.reg .pred p;\nsetp.ne.u32 p, %0, 0;\n@p mbarrier.arrive.shared::cluster.b64 _, [%0];\n}\n" ::"r"(bar) : "memory");
}
__device__ __forceinline__ void lds128(uint32_t* v, uint32_t addr) {
  asm volatile("ld.shared.v4.b32 {%0, %1, %2, %3}, [%4];\n" : "=r"(v[0]), "=r"(v[1]), "=r"(v[2]), "=r"(v[3]) : "r"(addr) : "memory");
}
__device__ __forceinline__ void sts128(uint32_t addr, const uint32_t* v) {
  asm volatile("st.shared.v4.b32 [%0], {%1, %2, %3, %4};\n" ::"r"(addr), "r"(v[0]), "r"(v[1]), "r"(v[2]), "r"(v[3]) : "memory");
}
__device__ __forceinline__ __nv_bfloat162 as_bf2(uint32_t v) { return *reinterpret_cast<__nv_bfloat162*>(&v); }
__device__ __forceinline__ uint32_t as_u32(__nv_bfloat162 v) { return *reinterpret_cast<uint32_t*>(&v); }
__device__ __forceinline__ uint32_t hfma2(uint32_t a, uint32_t b, uint32_t c) { return as_u32(__hfma2(as_bf2(a), as_bf2(b), as_bf2(c))); }
__device__ __forceinline__ uint32_t pack2(float a, float b) { return as_u32(__floats2bfloat162_rn(a, b)); }
__device__ __forceinline__ bool elect_one() {
  uint32_t r;
  asm volatile("{\n.reg .pred p;\nelect.sync _|p, 0xffffffff;\nselp.u32 %0, 1, 0, p;\n}\n" : "=r"(r));
  return r != 0;
}
__device__ __forceinline__ void wgmma_rs(float* d, const uint32_t* a, uint64_t bdesc, int accumulate = 1) {
  asm volatile(
      "{\n.reg .pred p;\nsetp.ne.b32 p, %53, 0;\n"
      "wgmma.mma_async.sync.aligned.m64n96k16.f32.bf16.bf16 " ACC_LIST "{%48, %49, %50, %51}, %52, p, 1, 1, 1;\n}\n"
      : ACC_OPERANDS("+f", d)
      : "r"(a[0]), "r"(a[1]), "r"(a[2]), "r"(a[3]), "l"(bdesc), "r"(accumulate));
}
__device__ __forceinline__ void ldsm4(uint32_t* r, uint32_t addr) {
  asm volatile("ldmatrix.sync.aligned.m8n8.x4.shared.b16 {%0, %1, %2, %3}, [%4];\n"
               : "=r"(r[0]), "=r"(r[1]), "=r"(r[2]), "=r"(r[3])
               : "r"(addr)
               : "memory");
}
__device__ __forceinline__ void lds64(uint32_t* v, uint32_t addr) {
  asm volatile("ld.shared.v2.b32 {%0, %1}, [%2];\n" : "=r"(v[0]), "=r"(v[1]) : "r"(addr) : "memory");
}
__device__ __forceinline__ void sts64(uint32_t addr, uint32_t a, uint32_t b) {
  asm volatile("st.shared.v2.b32 [%0], {%1, %2};\n" ::"r"(addr), "r"(a), "r"(b) : "memory");
}
__device__ __forceinline__ void sts32(uint32_t addr, uint32_t v) {
  asm volatile("st.shared.u32 [%0], %1;\n" ::"r"(addr), "r"(v) : "memory");
}
__device__ __forceinline__ uint32_t hadd2(uint32_t a, uint32_t b) { return as_u32(__hadd2(as_bf2(a), as_bf2(b))); }
__device__ __forceinline__ uint32_t hsub2(uint32_t a, uint32_t b) { return as_u32(__hsub2(as_bf2(a), as_bf2(b))); }
__device__ __forceinline__ uint32_t hmin2(uint32_t a, uint32_t b) { return as_u32(__hmin2(as_bf2(a), as_bf2(b))); }
__device__ __forceinline__ uint32_t hmax2(uint32_t a, uint32_t b) { return as_u32(__hmax2(as_bf2(a), as_bf2(b))); }
__device__ __forceinline__ uint32_t hfma2_lo(uint32_t w, uint32_t a, uint32_t c) {
  return as_u32(__hfma2(__low2bfloat162(as_bf2(w)), as_bf2(a), as_bf2(c)));
}
__device__ __forceinline__ uint32_t hfma2_hi(uint32_t w, uint32_t a, uint32_t c) {
  return as_u32(__hfma2(__high2bfloat162(as_bf2(w)), as_bf2(a), as_bf2(c)));
}
__device__ __forceinline__ uint32_t prmt(uint32_t a, uint32_t b, uint32_t sel) {
  uint32_t r;
  asm("prmt.b32 %0, %1, %2, %3;\n" : "=r"(r) : "r"(a), "r"(b), "r"(sel));
  return r;
}
__device__ __forceinline__ constexpr uint32_t tap_delta(int a, int b) {
  return (a == 0 ? 0xbf80u : a == 1 ? 0u : 0x3f80u) | (b == 0 ? 0xbf800000u : b == 1 ? 0u : 0x3f800000u);
}
__device__ __forceinline__ int thread_id() {
  int t;
  asm volatile("mov.u32 %0, %%tid.x;\n" : "=r"(t));
  return t;
}
__device__ __forceinline__ void proxy_fence() { asm volatile("fence.proxy.async.shared::cta;\n" ::: "memory"); }
template <int PITCH>
__device__ __forceinline__ void stage16(const float* acc, int jp, uint32_t stg) {
  uint32_t pk[4];
#pragma unroll
  for (int i = 0; i < 4; i++) pk[i] = pack2(acc[jp * 8 + i * 2], acc[jp * 8 + i * 2 + 1]);
  asm volatile("stmatrix.sync.aligned.m8n8.x4.shared.b16 [%0], {%1, %2, %3, %4};\n" ::"r"((stg ^ ((jp & 1) * 32)) + (jp >> 1) * PITCH),
               "r"(pk[0]), "r"(pk[1]), "r"(pk[2]), "r"(pk[3])
               : "memory");
}
__device__ __forceinline__ uint32_t swz(uint32_t a, uint32_t chunk) { return a | (((chunk ^ (a >> 7)) & 3) << 4); }
__device__ __forceinline__ void fma_ip(float& d, float c, float a) { asm volatile("fma.rn.f32 %0, %1, %2, %0;\n" : "+f"(d) : "f"(c), "f"(a)); }
__device__ __forceinline__ void fma_sc(float& d, float c, float a) { asm volatile("fma.rn.f32 %0, %1, %0, %2;\n" : "+f"(d) : "f"(c), "f"(a)); }

__device__ __forceinline__ void v_load(uint32_t (*d)[2], const uint32_t* a, uint32_t a5, uint32_t off) {
#pragma unroll
  for (int j = 0; j < 6; j++) lds64(d[j], (j == 5 ? a5 : a[j & 3]) + (j >> 2) * 4 * PLANE + off);
}
__device__ __forceinline__ void v_store(uint32_t (*d)[2], const uint32_t* a, uint32_t o05, uint32_t o34, uint32_t off) {
#pragma unroll
  for (int i = 0; i < 2; i++)
    asm volatile(
        "{\n.reg .b32 p, q, r, c;\n"
        "add.rn.bf16x2 %0, %0, %4;\n"
        "add.rn.bf16x2 %5, %5, %1;\n"
        "mov.b32 c, 0xc080c080;\n"
        "fma.rn.bf16x2 p, c, %2, %4;\n"
        "fma.rn.bf16x2 q, c, %1, %3;\n"
        "mov.b32 c, 0xc088c088;\n"
        "fma.rn.bf16x2 %0, c, %2, %0;\n"
        "fma.rn.bf16x2 %5, c, %3, %5;\n"
        "mov.b32 c, 0xbe80be80;\n"
        "fma.rn.bf16x2 r, c, %2, %4;\n"
        "fma.rn.bf16x2 %3, c, %1, %3;\n"
        "mov.b32 c, 0x3f003f00;\n"
        "fma.rn.bf16x2 %1, c, q, p;\n"
        "mov.b32 c, 0xbf00bf00;\n"
        "fma.rn.bf16x2 %2, c, q, p;\n"
        "mov.b32 c, 0x40004000;\n"
        "fma.rn.bf16x2 %4, c, %3, r;\n"
        "mov.b32 c, 0xc000c000;\n"
        "fma.rn.bf16x2 %3, c, %3, r;\n}\n"
        : "+r"(d[0][i]), "+r"(d[1][i]), "+r"(d[2][i]), "+r"(d[3][i]), "+r"(d[4][i]), "+r"(d[5][i]));
  sts64(a[0] + o05 + off, d[0][0], d[0][1]);
  sts64(a[1] + o05 + off, d[5][0], d[5][1]);
  sts64(a[2] + off, d[1][0], d[1][1]);
  sts64(a[3] + off, d[2][0], d[2][1]);
  sts64(a[0] + o34 + off, d[4][0], d[4][1]);
  sts64(a[1] + o34 + off, d[3][0], d[3][1]);
}
__device__ __forceinline__ void u_math16(const uint32_t (*g)[4], uint32_t dst) {
  uint32_t u[4][4];
#pragma unroll
  for (int i = 0; i < 4; i++) {
    const uint32_t s = hfma2(0x3e803e80u, g[2][i], g[0][i]), t = hfma2(0x3e803e80u, g[0][i], g[2][i]);
    u[0][i] = hfma2(0x3f003f00u, g[1][i], s);
    u[1][i] = hfma2(0xbf00bf00u, g[1][i], s);
    u[2][i] = hfma2(0x3f003f00u, g[1][i], t);
    u[3][i] = hfma2(0xbf00bf00u, g[1][i], t);
  }
#pragma unroll
  for (int k = 0; k < 4; k++) sts128(dst + k * SLOT, u[k]);
}

__device__ __forceinline__ void ldg128(uint32_t* v, const uint4* p) {
  asm volatile("ld.global.nc.v4.b32 {%0, %1, %2, %3}, [%4];\n" : "=r"(v[0]), "=r"(v[1]), "=r"(v[2]), "=r"(v[3]) : "l"(p));
}
__device__ __forceinline__ uint32_t lds32(uint32_t addr) {
  uint32_t v;
  asm volatile("ld.shared.u32 %0, [%1];\n" : "=r"(v) : "r"(addr) : "memory");
  return v;
}
__device__ __forceinline__ void ldsm4_if(uint32_t* r, uint32_t addr, uint32_t on) {
  asm volatile(
      "{\n.reg .pred p;\nsetp.ne.u32 p, %5, 0;\n"
      "@p ldmatrix.sync.aligned.m8n8.x4.shared.b16 {%0, %1, %2, %3}, [%4];\n}\n"
      : "+r"(r[0]), "+r"(r[1]), "+r"(r[2]), "+r"(r[3])
      : "r"(addr), "r"(on)
      : "memory");
}
__device__ __forceinline__ uint32_t hmul2_lo(uint32_t w, uint32_t a) { return as_u32(__hmul2(__low2bfloat162(as_bf2(w)), as_bf2(a))); }
__device__ __forceinline__ uint32_t clip2(uint32_t p) { return hmin2(hmax2(p, 0u), 0x435f435fu); }
__device__ __forceinline__ uint32_t frac2(uint32_t pos) {
  const float py = bf16lo(pos), px = bf16hi(pos);
  return __byte_perm(__float_as_uint(py - floorf(py)), __float_as_uint(px - floorf(px)), 0x7632);
}
__device__ __forceinline__ void coefs(uint32_t w, uint32_t& p0, uint32_t& p1) {
  const uint32_t o = hsub2(0x3f803f80u, w), xa = __byte_perm(o, w, 0x7632);
  p0 = hmul2_lo(o, xa);
  p1 = hmul2_lo(w, xa);
}
__device__ __forceinline__ uint32_t blend(uint32_t p0, uint32_t p1, uint32_t t, uint32_t g, uint32_t h, uint32_t k) {
  return hfma2_hi(p1, k, hfma2_lo(p1, h, hfma2_hi(p0, g, hmul2_lo(p0, t))));
}
__device__ __forceinline__ void st_pair(uint2* p, uint32_t a, uint32_t b) {
  asm volatile("st.relaxed.gpu.global.v2.u32 [%0], {%1, %2};\n" ::"l"(p), "r"(a), "r"(b) : "memory");
}
__device__ __forceinline__ void ld_pair(uint32_t* v, const uint2* p) {
  asm volatile("ld.relaxed.gpu.global.v2.u32 {%0, %1}, [%2];\n" : "=r"(v[0]), "=r"(v[1]) : "l"(p) : "memory");
}
__device__ __forceinline__ uint32_t request(Scratch* scr, uint32_t epoch, uint32_t pos, int h, int w, int tap) {
  const uint32_t slot = min(atomicAdd(scr->ready + 8 + ((epoch >> 7) & 1), 1u), QUEUE);
  if (slot < QUEUE) st_pair(scr->req + slot, pos, 0x80000000u | (h << 12) | (w << 4) | tap);
  return slot;
}
__device__ __forceinline__ uint32_t count_up(uint32_t addr) {
  uint32_t i;
  asm volatile("atom.shared.add.u32 %0, [%1], 1;\n" : "=r"(i) : "r"(addr) : "memory");
  return i;
}
__device__ __forceinline__ void patch(uint32_t id, uint32_t id0, uint32_t n, uint32_t base, uint32_t pitch, uint32_t ctl, int lane) {
  uint32_t todo = __ballot_sync(0xffffffffu, id - id0 < n);
  if (!todo) return;
#pragma unroll 1
  do {
    const int i0 = __ffs(todo) - 1;
    todo &= todo - 1;
    const uint32_t p0 = __shfl_sync(0xffffffffu, id, i0), other = todo & __ballot_sync(0xffffffffu, id != p0);
    const int i1 = __ffs(other) - 1;
    todo &= ~(other & -other);
    const uint32_t p1 = __shfl_sync(0xffffffffu, id, i1);
    if ((lane & 15) < 12 && (lane < 16 || other)) {
      const uint32_t a = swz(base + ((lane >> 2) & 3) * pitch + ((lane < 16 ? p0 : p1) - id0) * 64, lane);
      uint32_t v[4], c[4];
      lds128(v, a);
      lds128(c, ctl + O_COR + (lane < 16 ? i0 : i1) * 192 + (lane & 15) * 16);
#pragma unroll
      for (int k = 0; k < 4; k++) v[k] = hadd2(v[k], c[k]);
      sts128(a, v);
    }
    __syncwarp();
  } while (todo);
  proxy_fence();
  __syncwarp();
}

struct Maps {
  CUtensorMap x, w, wc, wt, out, off, col, gx, gout;
  CUtensorMap bx[2], bw[2], bout[2];
};

__global__ void __launch_bounds__(NTHREADS, 1)
dcn_kernel(const uint4* __restrict__ x, const uint32_t* __restrict__ offs, const uint4* __restrict__ wgt, Scratch* __restrict__ scr, uint32_t* tsp, const uint32_t never,
           const __grid_constant__ Maps tm) {
  extern __shared__ __align__(1024) uint8_t smem[];
  constexpr uint32_t sbase = 1024;
  constexpr uint32_t bars = sbase + SM_BAR;
  const int tid = threadIdx.x;
  const int bk = blockIdx.x >> 1;
  const int cta = MIX ? (blockIdx.x & 1 ? (bk < 4 ? bk + 56 : bk < 60 ? bk - 4 : bk + 66) : bk + 60) : blockIdx.x;
  const uint32_t tstart = clock32();
  const int wid = __shfl_sync(0xffffffffu, tid >> 5, 0);
  const int lane = tid & 31;
  const int ri = cta - NI, ry = ri / 3, x0 = 32 + (ri - ry * 3) * 64, y0 = 32 + ry * 8;
  const int band = cta >= 24, g0 = 32 + (cta - band * 24) * 8;
  if (wid == 12 && cta >= NI) {
    if (elect_one()) {
      mbar_init(bars + (B_WF + 1) * 8, 1);
      mbar_init(bars + B_XF * 8, 1);
      asm volatile("fence.mbarrier_init.release.cluster;\n" ::: "memory");
      mbar_expect_tx(bars + (B_WF + 1) * 8, 6 * SLOT);
      mbar_expect_tx(bars + B_XF * 8, UNIT);
      tma_load_3d(sbase + SM_RAW, &tm.w, bars + (B_WF + 1) * 8, 0, 0, 0);
      tma_load_3d(sbase + SM_V, &tm.x, bars + B_XF * 8, 0, x0 - 1, y0 + (ry & 1) * 4 - 1);
    }
    asm volatile("bar.arrive 0, 512;\n" ::: "memory");
  }
  if (wid == 12 && cta < NI - 4) {
    if (elect_one() && cta < 48) {
      mbar_init(bars + B_WF * 8, 1);
      mbar_init(bars + B_XF * 8, 1);
      asm volatile("fence.mbarrier_init.release.cluster;\n" ::: "memory");
      mbar_expect_tx(bars + B_WF * 8, 2 * SLOT);
      mbar_expect_tx(bars + B_XF * 8, YSLICE);
      while (clock32() - tstart < YX0) {}
      if (YORD) tma_load_3d(sbase + SM_YX, &tm.bx[band], bars + B_XF * 8, 0, g0 - 1, -2);
      tma_load_5d(sbase, &tm.bw[band], bars + B_WF * 8, 0, 0, 0);
      tma_load_5d(sbase + SLOT, &tm.bw[band], bars + B_WF * 8, 16, 0, 0);
      if (!YORD) tma_load_3d(sbase + SM_YX, &tm.bx[band], bars + B_XF * 8, 0, g0 - 1, -2);
    }
    asm volatile("bar.arrive 0, 512;\n" ::: "memory");
  }
  if (wid == 12 && cta >= NI - 4 && cta < NI) {
    if (elect_one()) {
#pragma unroll
      for (int c = 0; c < 4; c++) mbar_init(bars + c * 8, 1);
      asm volatile("fence.mbarrier_init.release.cluster;\n" ::: "memory");
      if (cta < NI - 1) {
#pragma unroll
        for (int c = 0; c < 4; c++) {
          mbar_expect_tx(bars + c * 8, SLOT);
          tma_load_4d(sbase + c * SLOT, &tm.wc, bars + c * 8, (c + 2) * 24, cta - (NI - 4), 0);
        }
      } else {
#pragma unroll
        for (int i = 0; i < 6; i++) {
          if (!(i & 1)) mbar_expect_tx(bars + i * 4, 2 * SLOT);
          tma_load_5d(sbase + i * SLOT, &tm.bw[1], bars + (i >> 1) * 8, 32 + (i & 1) * 16, 0, i >> 1);
        }
        mbar_expect_tx(bars + 3 * 8, 28672 + 16128);
        tma_load_3d(sbase + 18 * SLOT, &tm.col, bars + 3 * 8, 0, 9, 0);
        bulk_load<16128>(sbase + 18 * SLOT + 28672, offs + 32 * IW * 9, bars + 3 * 8);
      }
    }
  }
  const int f = wid * 4 + (lane >> 3), g = g0 + (lane & 7);
  uint32_t o9[9];
  if (cta < 48 && wid < 8) {
    const uint32_t* op = offs + (band ? g * IW + f : f * IW + g) * 9;
#pragma unroll
    for (int a = 0; a < 3; a++)
#pragma unroll
      for (int b = 0; b < 3; b++) o9[a * 3 + b] = __ldg(op + (band ? b * 3 + a : a * 3 + b));
  }
  if (cta >= 48 && cta < NI - 4 && tid < 36) asm volatile("prefetch.global.L2 [%0];\n" ::"l"(offs + ((cta & 7) * 4 + tid / 9) * IW * 9 + tid % 9 * 32));
  if (cta >= NI - 4 && cta < NI) {
    const int kj = cta - (NI - 4);
    if (kj == 3) {
      uint32_t epoch;
      asm volatile("ld.relaxed.gpu.global.u32 %0, [%1];\n" : "=r"(epoch) : "l"(scr->ready + 3) : "memory");
      epoch = (epoch & ~127u) + 128;
      if (tid < GRID) sts32(bars + 64 + tid * 4, epoch & never);
      __syncthreads();
      if (wid != 12) {
        const int t = tid - (wid > 12 ? 32 : 0);
        mbar_wait(bars + 3 * 8);
#pragma unroll 1
        for (int col = 0; col < 2; col++) {
          const int eh = col ? t >> 1 : 32 + (t >= 224), ew = col ? 32 + (t & 1) : t % 224;
          if (t >= 448 || (col && eh >> 1 == 16)) continue;
          const int client = eh < 32 ? 0 : ew < 32 ? 24 : NI + ((eh - 32) >> 3) * 3 + ((ew - 32) >> 6);
          const uint32_t base = pack2((float)eh, (float)ew), src = sbase + 18 * SLOT + (col ? eh * 128 + (t & 1) * 36 : 28672 + t * 36);
          const uint32_t id = eh < 32 ? eh * 8 + ew - 32 : ew < 32 ? ew * 8 + eh - 32 : (eh & 7) * 64 + ((ew - 32) & 63);
          uint32_t mask = 0;
#pragma unroll
          for (int m = 0; m < 9; m++) {
            const uint32_t gp = hadd2(base, tap_delta(m / 3, m % 3));
            o9[m] = clip2(hadd2(gp, lds32(src + m * 4)));
            const uint32_t d = __byte_perm(hsub2(o9[m], hmin2(gp, 0x435f435fu)), 0, ew < 32 ? 0x1032 : 0x3210) & 0x7fff7fffu;
            mask |= d > (client < NI ? 0x3f80u : 0u) ? 1u << m : 0u;
          }
#pragma unroll 1
          for (; mask; mask &= mask - 1) {
            const int m = __ffs(mask) - 1;
            const uint32_t i = count_up(bars + 64 + client * 4);
            uint32_t pos = o9[0];
#pragma unroll
            for (int k = 1; k < 9; k++) pos = m == k ? o9[k] : pos;
            if (i >= MAXEX) break;
            st_pair(scr->mail[client] + i, id | (request(scr, epoch, pos, eh, ew, m) << 16), epoch);
          }
        }
        __syncwarp();
        asm volatile("bar.sync 1, 480;\n" ::: "memory");
        if (tid < GRID) st_pair(scr->mail[tid] + MAXEX, lds32(bars + 64 + tid * 4), epoch);
        TSE(2);
      }
      if (wid == 12 && elect_one()) {
#pragma unroll 1
        for (int r = 0; r < 3; r++) {
          const int sl = r == 2 ? 0 : r + 1;
#pragma unroll
          for (int ki = 0; ki < 3; ki++) {
            mbar_wait(bars + ki * 8, r & 1);
            if (sl || ki != 1) bulk_store<2 * SLOT>(scr->w + (ki * 6 + sl * 2) * 576, sbase + (r * 6 + ki * 2) * SLOT);
          }
          asm volatile("cp.async.bulk.commit_group;\n" ::: "memory");
          if (r < 2) {
#pragma unroll
            for (int i = 0; i < 6; i++) {
              if (!(i & 1)) mbar_expect_tx(bars + i * 4, 2 * SLOT);
              tma_load_5d(sbase + (r * 6 + 6 + i) * SLOT, &tm.bw[1], bars + (i >> 1) * 8, (r ? 0 : 64) + (i & 1) * 16, 0, i >> 1);
            }
          }
          asm volatile("cp.async.bulk.wait_group 0;\n" ::: "memory");
          asm volatile(REDSEM ".gpu.global.add.u32 [%0], 128;\n" ::"l"(scr->ready + 3 + r) : "memory");
          TSE(r);
        }
      }
      return;
    }
    uint32_t epoch;
    asm volatile("ld.relaxed.gpu.global.u32 %0, [%1];\n" : "=r"(epoch) : "l"(scr->ready) : "memory");
    epoch = (epoch & ~127u) + 128;
    if (tid == 0) {
      mbar_init(bars + 4 * 8, 1);
      if (kj == 0) scr->ready[8 + ((epoch >> 7) & 1 ^ 1)] = 0;
    }
    __syncthreads();
    {
      if (wid < 12) {
        const int half = wid >= 6, q = tid - half * 192;
#pragma unroll 1
        for (int c = half; c < 4; c += 2) {
          uint4 g[3], u[4];
          mbar_wait(bars + c * 8);
#pragma unroll
          for (int k = 0; k < 3; k++) lds128(&g[k].x, sbase + c * SLOT + k * 3072 + (q >> 6) * 64 + ((q >> 2) & 15) * 192 + (q & 3) * 16);
#pragma unroll
          for (int i = 0; i < 4; i++) {
            float o[4][2];
#pragma unroll
            for (int e = 0; e < 2; e++) {
              const float a = e ? bf16hi((&g[0].x)[i]) : bf16lo((&g[0].x)[i]), bb = e ? bf16hi((&g[1].x)[i]) : bf16lo((&g[1].x)[i]);
              const float cc = e ? bf16hi((&g[2].x)[i]) : bf16lo((&g[2].x)[i]);
              const float s = fmaf(0.25f, cc, a), t = fmaf(0.25f, a, cc);
              o[0][e] = fmaf(0.5f, bb, s);
              o[1][e] = fmaf(-0.5f, bb, s);
              o[2][e] = fmaf(0.5f, bb, t);
              o[3][e] = fmaf(-0.5f, bb, t);
            }
#pragma unroll
            for (int k = 0; k < 4; k++) (&u[k].x)[i] = pack2(o[k][0], o[k][1]);
          }
          const uint32_t out = sbase + 18 * SLOT + c * 12288;
#pragma unroll
          for (int k = 0; k < 4; k++) sts128(out + k * 3072 + (q ^ ((q >> 3) & 3)) * 16, &u[k].x);
          proxy_fence();
          asm volatile("bar.arrive %0, 224;\n" ::"r"(1 + c) : "memory");
        }
      } else {
        const int c = wid - 12;
        asm volatile("bar.sync %0, 224;\n" ::"r"(1 + c) : "memory");
        if (elect_one()) {
#pragma unroll
          for (int k = 0; k < 4; k++) bulk_store<3072>(scr->u + (c * 4 + k) * 576 + kj * 192, sbase + 18 * SLOT + c * 12288 + k * 3072);
          asm volatile("cp.async.bulk.commit_group;\ncp.async.bulk.wait_group 0;\n" ::: "memory");
          asm volatile(REDSEM ".gpu.global.add.u32 [%0], %1;\n" ::"l"(scr->ready + min(c, 2)), "r"((kj ? 32 : 64) >> (c >> 1)) : "memory");
          TSE(0);
        }
      }
    }
    if (wid < 12) asm volatile("bar.sync 5, 384;\n" ::: "memory");
    if (tid == 0) {
      mbar_expect_tx(bars + 4 * 8, 18 * SLOT);
#pragma unroll
      for (int sl = 0; sl < 3; sl++) tma_load_3d(sbase + sl * 6 * SLOT, &tm.w, bars + 4 * 8, 0, sl * 48, 0);
    }
    const uint32_t dl = sbase + 18 * SLOT + 4 * 12288 + wid * 384;
#pragma unroll 1
    for (int slot = wid * 3 + kj; slot < QUEUE; slot += 48) {
      uint2 rq;
#pragma unroll 1
      for (uint32_t spin = 0;; spin++) {
        uint32_t done, total;
        asm volatile("ld.relaxed.gpu.global.v2.u32 {%0, %1}, [%2];\n" : "=r"(rq.x), "=r"(rq.y) : "l"(scr->req + slot) : "memory");
        asm volatile("ld.acquire.gpu.global.u32 %0, [%1];\n" : "=r"(done) : "l"(scr->ready + 6) : "memory");
        if (rq.y) break;
        if (done == epoch) {
          asm volatile("ld.relaxed.gpu.global.u32 %0, [%1];\n" : "=r"(total) : "l"(scr->ready + 8 + ((epoch >> 7) & 1)) : "memory");
          if (slot >= total) break;
        }
        if (spin > (1u << 22)) __trap();
        __nanosleep(100);
      }
      if (!rq.y) break;
      __syncwarp();
      TSE(4);
      if (lane == 0) scr->req[slot] = make_uint2(0, 0);
      const int tap = rq.y & 15, ki = (tap * 11) >> 5, gy = (int)bf16lo(rq.x), gx = (int)bf16hi(rq.x);
      const int cy = min(max((int)((rq.y >> 12) & 255) + ki - 1, 0), IH - 1), cx = min(max((int)((rq.y >> 4) & 255) + tap - ki * 3 - 1, 0), IW - 1);
      if (lane < 24) {
        const uint2* pc = reinterpret_cast<const uint2*>(x) + lane;
        const int p = (gy * IW + gx) * 24, sx = gx < IW - 1 ? 24 : 0, sy = gy < IH - 1 ? IW * 24 : 0;
        const uint2 v0 = __ldg(pc + p), v1 = __ldg(pc + p + sx), v2 = __ldg(pc + p + sy), v3 = __ldg(pc + p + sy + sx);
        const uint2 c = __ldg(pc + (cy * IW + cx) * 24);
        uint32_t q0, q1;
        coefs(frac2(rq.x), q0, q1);
        const uint32_t d0 = hsub2(blend(q0, q1, v0.x, v1.x, v2.x, v3.x), c.x), d1 = hsub2(blend(q0, q1, v0.y, v1.y, v2.y, v3.y), c.y);
        const uint32_t dd[4] = {__byte_perm(d0, 0, 0x1010), __byte_perm(d0, 0, 0x3232), __byte_perm(d1, 0, 0x1010), __byte_perm(d1, 0, 0x3232)};
        sts128(dl + lane * 16, dd);
      }
      __syncwarp();
      TSE(5);
      mbar_wait(bars + 4 * 8);
      TSE(6);
      float sum[8] = {};
      const int l24 = min(lane, 23);
#pragma unroll 1
      for (int b = 0; b < 6; b++) {
        uint32_t part[4] = {};
#pragma unroll
        for (int i = 0; i < 8; i++) {
          uint32_t wv[4];
          lds128(wv, sbase + (b >> 1) * 6 * SLOT + tap * 6144 + (b & 1) * 3072 + i * 384 + l24 * 16);
          const uint32_t d = lds32(dl + (b * 16 + i * 2 + (l24 >= 12)) * 4);
#pragma unroll
          for (int k = 0; k < 4; k++) part[k] = hfma2(d, wv[k], part[k]);
        }
#pragma unroll
        for (int k = 0; k < 4; k++) {
          sum[k * 2] += bf16lo(part[k]);
          sum[k * 2 + 1] += bf16hi(part[k]);
        }
      }
#pragma unroll
      for (int k = 0; k < 8; k++) sum[k] += __shfl_down_sync(0xffffffffu, sum[k], 12);
      if (lane < 12) {
#pragma unroll
        for (int k = 0; k < 4; k++)
          asm volatile("st.relaxed.gpu.global.v2.u32 [%0], {%1, %2};\n" ::"l"(scr->res[slot] + lane * 4 + k), "r"(pack2(sum[k * 2], sum[k * 2 + 1])), "r"(epoch) : "memory");
      }
      TSE(1);
    }
    mbar_wait(bars + 4 * 8);
  } else if (wid < 8) {
    const int wg = wid >> 2, warp = wid & 3;
    if (cta < 48) {
    uint32_t cf[36];
#pragma unroll
    for (int i = 0; i < 9; i++) cf[i] = o9[i];
    asm volatile("bar.sync 0, 512;\n" ::: "memory");
    {
      const uint32_t base = pack2((float)f, (float)g), sel = band ? 0x1032u : 0x3210u;
      const uint32_t tab = sbase + SM_YT + wid * 1152;
      uint32_t bad = 0;
#pragma unroll
      for (int a = 0; a < 3; a++)
#pragma unroll
        for (int b = 0; b < 3; b++) {
          const uint32_t gp = hadd2(base, tap_delta(a, b));
          const uint32_t pos = hmin2(hmax2(hadd2(gp, __byte_perm(cf[a * 3 + b], 0, sel)), 0u), 0x435f435fu);
          uint32_t d = hsub2(pos, hmin2(gp, 0x435f435fu));
          if ((d & 0x7fff7fffu) > 0x3f80u) {
            bad = 1;
            d = a == 0 && f == 0 ? 0x3f80u : 0u;
          }
          sts32(tab + (lane & 7) * 144 + (b * 12 + (lane >> 3) * 3 + a) * 4, YPRMT ? (d << 16) | (d & 0x8000u ? 0x3210u : 0x7654u) : hmin2(hmax2(__byte_perm(d, 0, 0x1010), 0x0000ff80u), 0x7f800000u));
        }
      if (bad && g >= 34) sts32(bars + O_CNT, FAILED);
      __syncwarp();
      arrive_if(lane == 0 ? bars + B_OS * 8 : 0u);
      asm volatile("setmaxnreg.inc.sync.aligned.u32 224;\n");
      __syncwarp();
#pragma unroll
      for (int i = 0; i < 9; i++) lds128(cf + i * 4, tab + (lane >> 2) * 144 + i * 16);
    }
    uint32_t xa[3];
#pragma unroll
    for (int b = 0; b < 3; b++)
      xa[b] = swz(sbase + SM_YX + ((wid * 4 + (lane >> 4)) * 10 + min((lane & 7) + b, IW - g0)) * 64, (lane >> 3) & 1);
    float acc[2][48];
    uint32_t X[2][16], A[2][12];
    auto fetch = [&](uint32_t* r, uint32_t a) {
#pragma unroll
      for (int i = 0; i < 4; i++) ldsm4(r + i * 4, (a ^ ((i & 1) * 32)) + i * 1280);
    };
    uint64_t bd = w_desc(sbase);
    uint32_t wf = bars + B_WF * 8;
    mbar_wait(bars + B_XF * 8);
    if (YLAG && wg) { const uint32_t t1 = clock32(); wait_until(t1, YLAG); }
    TSE(0);
    fetch(X[0], xa[0]);
    mbar_wait(wf);
#pragma unroll 1
    for (int s = 0; s < 3; s++) {
#pragma unroll
      for (int n = 0; n < 6; n++) {
        const int b = n >> 1;
        if (n == 5) {
          mbar_wait(bars + (B_XF + min(s + 1, 2)) * 8);
#pragma unroll
          for (int k = 0; k < 3; k++) xa[k] += s < 2 ? YSLICE : 0;
        }
        fetch(X[~n & 1], xa[(n + 1) % 6 >> 1] ^ ((~n & 1) * 32));
        const uint32_t* xr = X[n & 1];
        uint32_t D[7][2];
#pragma unroll
        for (int j = 0; j < 7; j++)
#pragma unroll
          for (int e = 0; e < 2; e++) D[j][e] = hsub2(xr[(j + 1) * 2 + e], xr[j * 2 + e]);
#pragma unroll
        for (int t = 0; t < 2; t++) {
          wgmma_wait<1>();
#pragma unroll
          for (int a = 0; a < 3; a++)
#pragma unroll
            for (int i = 0; i < 4; i++) {
              const int o = t * 2 + (i & 1), e = i >> 1, j = o + a + 1;
              const uint32_t c = cf[b * 12 + o * 3 + a];
              A[t][a * 4 + i] = YPRMT ? hfma2_hi(c, prmt(D[j - 1][e], D[j][e], c), xr[j * 2 + e]) : hfma2_hi(c, D[j][e], hfma2_lo(c, D[j - 1][e], xr[j * 2 + e]));
            }
          wgmma_fence();
#pragma unroll
          for (int a = 0; a < 3; a++) wgmma_rs(acc[t], A[t] + a * 4, bd + n * (SLOT >> 4) + a * 192, (n | a) ? 1 : s);
          wgmma_commit();
        }
        if (n & 1) mbar_wait(wf + (b + 1) * 8);
        if (n & 1) TSB(10 + s * 3 + b);
        if (n == 1 && s == 1 && elect_one()) arrive_if(bars + B_WE * 8);
      }
      bd += 6 * SLOT >> 4;
      wf += 24;
    }
    TSE(1);
    const int lane = thread_id() & 31;
    const uint32_t stg = sbase + wg * 3 * SLOT + (wid & 3) * 2048 + (lane & 15) * 64 + ((((lane >> 4) ^ (lane >> 1)) & 3) << 4);
    wgmma_wait<1>();
    acc_fence(acc[0]);
#pragma unroll
    for (int jp = 0; jp < 6; jp++) stage16<8192>(acc[0], jp, stg);
    wgmma_wait<0>();
    acc_fence(acc[1]);
#pragma unroll
    for (int jp = 0; jp < 6; jp++) stage16<8192>(acc[1], jp, stg + 1024);
    proxy_fence();
    __syncwarp();
    arrive_if(lane == 0 ? bars + (B_ST + wg * 4) * 8 : 0u);
    } else if (cta < NI) {
      asm volatile("bar.sync 0, 512;\n" ::: "memory");
      asm volatile("setmaxnreg.inc.sync.aligned.u32 224;\n");
    } else {
    const int tid = thread_id(), lane = tid & 31;
    {
      uint32_t g[3][3][4], src[3], dst[3];
#pragma unroll
      for (int r = 0; r < 3; r++) {
        const int q = r < 2 ? tid + r * 256 : 512 + (tid & 63), b = q >> 6, kj = (b * 11) >> 5;
        src[r] = sbase + SM_RAW + kj * (6144 - 192) + b * 64 + ((q >> 2) & 15) * 192 + (q & 3) * 16;
        dst[r] = sbase + SM_W + (q ^ ((q >> 3) & 3)) * 16;
      }
      asm volatile("bar.sync 0, 512;\n" ::: "memory");
      mbar_wait(bars + (B_WF + 1) * 8);
#pragma unroll 1
      for (int c = 0; c < 2; c++) {
        const bool extra = (wid >> 1) == 2 + c;
#pragma unroll
        for (int r = 0; r < 3; r++)
#pragma unroll
          for (int k = 0; k < 3; k++)
            if (r < 2 || extra) lds128(g[r][k], src[r] + c * 3072 + k * 2 * SLOT);
#pragma unroll
        for (int r = 0; r < 3; r++)
          if (r < 2 || extra) u_math16(g[r], dst[r] + c * 4 * SLOT);
        proxy_fence();
        __syncwarp();
        arrive_if(lane == 0 ? bars + (B_WF + c * 4) * 8 : 0u);
      }
    }
    asm volatile("setmaxnreg.inc.sync.aligned.u32 224;\n");
    float m[4][48];
    const uint32_t vb = sbase + SM_V + wg * UNIT;
    const uint64_t bd0 = w_desc(sbase + SM_W), ad12 = a_desc(vb + 2 * PLANE), ad05 = a_desc(vb + (wg ? 4 * PLANE : 0));

    const uint64_t d34 = wg ? -(2 * PLANE >> 4) : 2 * PLANE >> 4;
    uint64_t ad = ad12;
    uint32_t wf = bars + B_WF * 8;
#pragma unroll 1
    for (int sl = 0; sl < 3; sl++) {
      {
        uint32_t a[4], d[6][2];
#pragma unroll
        for (int j = 0; j < 4; j++) a[j] = swz(vb + j * PLANE + ((tid & 127) >> 3) * 64, lane >> 1) + (lane & 1) * 8;
        const uint32_t a5 = y0 == 216 && ((wg ^ ry) & 1) ? a[0] : a[1], o34 = wg ? 0 : 4 * PLANE;
        mbar_wait(bars + (B_XF + sl * 2 + wg) * 8);
#pragma unroll
        for (int i = 4 - VC; i < 4; i++) {
          v_load(d, a, a5, sl * 2 * UNIT + i * 1024);
          v_store(d, a, 4 * PLANE - o34, o34, sl * 2 * UNIT + i * 1024);
        }
        proxy_fence();
        __syncwarp();
        arrive_if(lane == 0 ? bars + (B_XR + sl * 2 + wg) * 8 : 0u);
        TSB(8 + sl * 3);
        mbar_wait(wf);
        mbar_wait(bars + (B_XR + sl * 2 + wg) * 8);
        TSB(9 + sl * 3);
      }
#pragma unroll
      for (int n = 0; n < 8; n++) {
        const int k = n & 3;
        wgmma_fence();
#pragma unroll
        for (int kj = 0; kj < 3; kj++)
          wgmma_ss(m[k], (k < 2 ? ad : ad + d34) + (k & 1) * (PLANE >> 4) + n / 4 * 2 + kj * 4, bd0 + n * (SLOT >> 4) + kj * 192, (n / 4 | kj) ? 1 : sl);
        wgmma_commit();
        if (n < 7) {
          if (sl || n == 3) mbar_wait(wf + (n + 1) * 8);
          wgmma_wait<1>();
          if (warp == 0 && n) asm volatile("bar.arrive %0, 96;\n" ::"r"(7 + n) : "memory");
        }
      }
      if (!LATE4 && sl == 2 && wg) asm volatile("bar.arrive 4, 256;\n" ::: "memory");
      wgmma_wait<1>();
      if (LATE4 && sl == 2 && wg) asm volatile("bar.arrive 4, 256;\n" ::: "memory");
      if (warp == 0) asm volatile("bar.arrive 14, 96;\n" ::: "memory");
      wgmma_wait<0>();
      if (warp == 0) asm volatile("bar.arrive 15, 96;\n" ::: "memory");
      TSB(10 + sl * 3);
      ad += 2 * UNIT >> 4;
      wf += 64;

    }
    const uint32_t stg = sbase + SM_X + 2 * UNIT + wg * 21504 + warp * 1024 + (lane & 15) * 64 + ((((lane >> 4) ^ (lane >> 1)) & 3) << 4);
    const uint32_t stb = lane == 0 ? bars + (B_ST + wg * 4) * 8 : 0u;
    auto publish = [&](int k) {
      proxy_fence();
      __syncwarp();
      arrive_if(stb ? stb + k * 8 : 0u);
    };
#pragma unroll
    for (int k = 0; k < 4; k++) acc_fence(m[k]);
    float dep = 0.f;
#pragma unroll
    for (int i0 = 0; i0 < 48; i0 += TGRP) {
#pragma unroll
      for (int e = 0; e < TX; e++) asm volatile("add.f32 %0, %0, %0;\n" : "+f"(dep));
      const float k0 = __uint_as_float((__float_as_uint(dep) & never) | 0xbf088889u);
      const float k1 = __uint_as_float((__float_as_uint(dep) & never) | 0xbf800000u);
#pragma unroll
      for (int i = i0; i < i0 + TGRP; i++) {
        m[0][i] *= k0;
        m[3][i] = fmaf(k1, m[3][i], m[2][i]);
        m[1][i] = fmaf(-8.0f / 15.0f, m[1][i], m[0][i]);
        m[2][i] = fmaf(-0.5f, m[3][i], m[2][i]);
        m[0][i] = fmaf(-0.5f, m[1][i], m[0][i]);
        m[1][i] = fmaf(4.0f / 15.0f, m[2][i], m[1][i]);
        m[0][i] = fmaf(4.0f / 15.0f, m[3][i], m[0][i]);
        m[2][i] = fmaf(0.25f, m[1][i], m[2][i]);
        m[3][i] = fmaf(0.25f, m[0][i], m[3][i]);
        dep = m[TDEP][i];
        if ((i & 7) == 7) {
          stage16<4096>(m[2], i >> 3, stg);
          stage16<4096>(m[0], i >> 3, stg + 2 * UNIT);
        }
      }
    }
    publish(0);
    TSB(20);
    asm volatile("bar.sync %0, 256;\n" ::"r"(4 + wg) : "memory");
    TSB(21);
    const uint64_t bdx = w_desc(sbase + SM_X);
    const uint32_t s05 = vb + (wg ? 4 * PLANE : 0) + warp * 1024 + (lane & 15) * 64;
#pragma unroll
    for (int j = 0; j < 12; j++) {
      float* acc = j < 6 ? m[1] : m[3];
      const int c = j % 6;
      const uint64_t ad = ad05 + (c >> 1) * (2 * UNIT >> 4) + (c & 1) * 2 + (j < 6 ? 0 : PLANE >> 4);
      const uint64_t bd = j == 0 ? bdx : j == 1 ? bdx + ((2 * UNIT + 12288) >> 4) : j < 10 ? bd0 + (j - 2) * (SLOT >> 4) : bdx + (j - 9) * (SLOT >> 4);
      if (j != 11) mbar_wait(bars + (B_WF + 24 + j) * 8);
      wgmma_fence();
#pragma unroll
      for (int kj = 0; kj < 3; kj++) wgmma_ss(acc, ad + kj * 4, bd + kj * 192);
      wgmma_commit();
      if (j == 3 || j == 5 || j == 7 || j == 9 || j == 11) TSB(22 + j);
      if (PW >= 0 && j < 11) wgmma_wait<PW < 0 ? 0 : PW>();
      if (j == HAND && !wg) asm volatile("bar.arrive 5, 256;\n" ::: "memory");
      if (Y0M == 0) {
        if (j == 7) {
          wgmma_wait<2>();
          acc_fence(m[1]);
        }
        if (j >= 7 && j <= 9) {
#pragma unroll
          for (int jp = j * 2 - 14; jp < j * 2 - 12; jp++) stage16<2 * UNIT>(m[1], jp, swz(s05, lane >> 4));
        }
      } else if (j == 5 + Y0M) {
        wgmma_wait<Y0M>();
        acc_fence(m[1]);
#pragma unroll
        for (int jp = 0; jp < 6; jp++) stage16<2 * UNIT>(m[1], jp, swz(s05, lane >> 4));
      }
      if (j == PUB1) publish(1);
    }
    wgmma_wait<0>();
    acc_fence(m[3]);
    const uint32_t tend = clock32();
    if (HAND == 13 && !wg) asm volatile("bar.arrive 5, 256;\n" ::: "memory");
#pragma unroll
    for (int jp = 0; jp < 6; jp++) stage16<2 * UNIT>(m[3], jp, swz(s05 + PLANE, lane >> 4));
    if (HAND == 12 && !wg) asm volatile("bar.arrive 5, 256;\n" ::: "memory");
    publish(2);
    }
    int rounds = 1;
    const int tid = thread_id(), lane = tid & 31;
    if (cta < 48 || cta >= NI) {
      mbar_wait(bars + B_OK * 8);
      rounds = lds32(bars + O_VER) != FAILED ? 0 : cta < 48 ? 2 : 4;
      rounds = __shfl_sync(0xffffffffu, rounds, 0);
    }
    if (rounds) {
      const bool lead = warp == 0 && elect_one();
      if (rounds > 1) {
        if (tid == 0) {
#pragma unroll
          for (int i = 0; i < 15; i++) mbar_init(bars + (B_G + i) * 8, 1);
          asm volatile("fence.mbarrier_init.release.cluster;\n" ::: "memory");
        }
        proxy_fence();
        asm volatile("bar.sync 3, 256;\n" ::: "memory");
      }
      const uint32_t win = sbase + SM_GX + wg * 3 * GSLICE, gxb = bars + (B_G + 9 + wg * 3) * 8;
      const uint64_t bd0 = w_desc(sbase);
      float acc[48];
#pragma unroll 1
      for (int r = 0; r < rounds; r++) {
        int ty, tx;
        if (cta >= NI) { ty = y0; tx = x0 + r * 16 + wg * 8; }
        else if (cta < 48) { ty = band ? g0 : r * 16 + wg * 8; tx = band ? r * 16 + wg * 8 : g0; }
        else { ty = (cta & 1) * 8 + wg * 16; tx = (cta & 2) * 4 + ((cta >> 2 ^ wg) & 1) * 16; }
        if (lead && rounds > 1) {
#pragma unroll 1
          for (int sl = 0; sl < 3; sl++) {
            mbar_expect_tx(gxb + sl * 8, GSLICE);
            tma_load_3d(win + sl * GSLICE, &tm.gx, gxb + sl * 8, sl * 32, tx - 2, ty - 2);
            if (r == 0) {
#pragma unroll 1
              for (int ki = 0; ki < 3; ki++) {
                if (!wg) mbar_expect_tx(bars + (B_G + sl * 3 + ki) * 8, 2 * SLOT);
                tma_load_5d(sbase + ((sl * 3 + ki) * 2 + wg) * SLOT, &tm.bw[1], bars + (B_G + sl * 3 + ki) * 8, sl * 32 + wg * 16, 0, ki);
              }
            }
          }
        }
        const int ph = ty + warp * 2 + ((lane >> 3) & 1), pw = tx + (lane & 7);
        const uint32_t* op = offs + (ph * IW + pw) * 9;
        const uint32_t base = pack2((float)ph, (float)pw);
        uint32_t ent[9], cf[36], need = 0, out = 0;
#pragma unroll
        for (int m = 0; m < 9; m++) ent[m] = __ldg(op + m);
#pragma unroll
        for (int m = 0; m < 9; m++) {
          const uint32_t pos = clip2(hadd2(hadd2(base, tap_delta(m / 3, m % 3)), ent[m])), fr = frac2(pos);
          const uint32_t iy = (int)bf16lo(pos) - (ty - 2), ix = (int)bf16hi(pos) - (tx - 2);
          out |= max(iy, ix) > 10;
          need |= ((fr >> 16 ? 1u : 0u) | (fr & 0xffffu ? 2u : 0u) | (fr >> 16 && (fr & 0xffffu) ? 4u : 0u)) << (m * 3);
          const uint32_t pp = (iy * 12 + ix) * 0x10001u + 0x10000u;
          ent[m] = (pp * 64 + ((pp << 3) & 0x300030u)) ^ ((lane >> 4) * 0x100010u);
          coefs(__shfl_sync(0xffffffffu, fr, lane >> 2), cf[m * 4], cf[m * 4 + 1]);
          coefs(__shfl_sync(0xffffffffu, fr, (lane >> 2) + 8), cf[m * 4 + 2], cf[m * 4 + 3]);
        }
        need = __reduce_or_sync(0xffffffffu, need);
        asm volatile("{\n.reg .pred p;\nsetp.ne.u32 p, %0, 0;\nbarrier.red.popc.u32 %0, %1, 128, p;\n}\n" : "+r"(out) : "r"(1 + wg) : "memory");
        out = __shfl_sync(0xffffffffu, out, 0);
        TSE(0);
        if (!out) {
          uint32_t C[2][4][8], A[2][8];
#pragma unroll
          for (int i = 0; i < 64; i++) C[0][0][i] = 0;
          auto fetch = [&](uint32_t (*c)[8], int m, uint32_t slice) {
            const uint32_t a0 = (ent[m] & 0xffffu) + slice, a1 = (ent[m] >> 16) + slice;
#pragma unroll
            for (int h = 0; h < 2; h++) {
              ldsm4(c[0] + h * 4, a0 ^ (h * 32));
              ldsm4_if(c[1] + h * 4, a1 ^ (h * 32), need & (1 << (m * 3)));
              ldsm4_if(c[2] + h * 4, (a0 ^ (h * 32) ^ 32) + 768, need & (2 << (m * 3)));
              ldsm4_if(c[3] + h * 4, (a1 ^ (h * 32) ^ 32) + 768, need & (4 << (m * 3)));
            }
          };
#pragma unroll 1
          for (int sl = 0; sl < 3; sl++) {
            const uint32_t slice = win + sl * GSLICE;
            const uint64_t bd = bd0 + sl * (6 * SLOT >> 4);
            mbar_wait(gxb + sl * 8, r & 1);
            fetch(C[0], 0, slice);
#pragma unroll
            for (int m = 0; m < 9; m++) {
              if (m < 8) fetch(C[~m & 1], m + 1, slice);
              if (m % 3 == 0) mbar_wait(bars + (B_G + sl * 3 + m / 3) * 8);
              if (m >= 2) wgmma_wait<1>();
#pragma unroll
              for (int i = 0; i < 8; i++)
                A[m & 1][i] = blend(cf[m * 4 + (i & 1) * 2], cf[m * 4 + (i & 1) * 2 + 1], C[m & 1][0][i], C[m & 1][1][i], C[m & 1][2][i], C[m & 1][3][i]);
              wgmma_fence();
              wgmma_rs(acc, A[m & 1], bd + m / 3 * (2 * SLOT >> 4) + m % 3 * 192, m ? 1 : sl);
              wgmma_rs(acc, A[m & 1] + 4, bd + (m / 3 * 2 + 1) * (SLOT >> 4) + m % 3 * 192);
              wgmma_commit();
            }
            wgmma_wait<0>();
          }
        } else {
#pragma unroll 1
          for (int i = 0; i < 12; i++) mbar_wait(i < 9 ? bars + (B_G + i) * 8 : gxb + (i - 9) * 8, i < 9 ? 0 : r & 1);
          const uint32_t scratch = win + warp * 3072 + lane * 16;
#pragma unroll 1
          for (int m = 0; m < 9; m++) {
            const int ki = (m * 11) >> 5;
            const uint32_t pos = clip2(hadd2(pack2((float)(ph + ki - 1), (float)(pw + m - ki * 3 - 1)), __ldg(op + m)));
            const int gy = (int)bf16lo(pos), gx = (int)bf16hi(pos), sx = gx < IW - 1 ? 12 : 0, sy = gy < IH - 1 ? IW * 12 : 0;
            const uint4* pc = x + (gy * IW + gx) * 12 + (lane >> 4);
            uint32_t q0, q1, V[6][4][4], A[6][4];
            coefs(frac2(pos), q0, q1);
#pragma unroll
            for (int k = 0; k < 6; k++)
#pragma unroll
              for (int c = 0; c < 4; c++) ldg128(V[k][c], pc + k * 2 + (c & 1) * sx + (c >> 1) * sy);
#pragma unroll
            for (int k = 0; k < 6; k++) {
#pragma unroll
              for (int i = 0; i < 4; i++) V[k][0][i] = blend(q0, q1, V[k][0][i], V[k][1][i], V[k][2][i], V[k][3][i]);
              sts128(scratch + k * 512, V[k][0]);
            }
            __syncwarp();
#pragma unroll
            for (int k = 0; k < 6; k++) ldsm4(A[k], scratch + k * 512);
            wgmma_fence();
#pragma unroll
            for (int k = 0; k < 6; k++) wgmma_rs(acc, A[k], bd0 + ((k >> 1) * 6 + ki * 2 + (k & 1)) * (SLOT >> 4) + (m - ki * 3) * 192, k ? 1 : m);
            wgmma_commit();
            wgmma_wait<0>();
          }
        }
        acc_fence(acc);
        TSE(1);
        asm volatile("bar.sync %0, 128;\n" ::"r"(1 + wg) : "memory");
#pragma unroll
        for (int jp = 0; jp < 6; jp++) stage16<4096>(acc, jp, win + warp * 1024 + (lane & 15) * 64 + ((((lane >> 4) ^ (lane >> 1)) & 3) << 4));
        proxy_fence();
        asm volatile("bar.sync %0, 128;\n" ::"r"(1 + wg) : "memory");
        if (lead) {
          tma_store(&tm.gout, win, tx, ty);
          asm volatile("cp.async.bulk.commit_group;\ncp.async.bulk.wait_group.read 0;\n" ::: "memory");
          TSE(2);
        }
      }
    }
  } else if (wid < 12) {
    asm volatile("setmaxnreg.dec.sync.aligned.u32 32;\n");
    const int tid = thread_id(), lane = tid & 31;

    const bool one = elect_one();
    if (one && cta < NI) {
#pragma unroll
      for (int i = 0; i < 4; i++) mbar_init(bars + (B_G + (wid - 8) * 4 + i) * 8, 1);
      asm volatile("fence.mbarrier_init.release.cluster;\n" ::: "memory");
    }
    if (one && cta >= NI) {
#pragma unroll
      for (int i = 0; i < 7; i++) mbar_init(bars + (B_WF + 8 + (wid - 8) * 7 + i) * 8, 1);
      if (wid < 10) mbar_init(bars + (B_WF + (wid - 8) * 4) * 8, 8);
      mbar_init(bars + (B_UR + wid - 8) * 8, wid == 11 ? 3 : 1);
      asm volatile("fence.mbarrier_init.release.cluster;\n" ::: "memory");
    }
    asm volatile("bar.arrive 3, 256;\n" ::: "memory");
    asm volatile("bar.sync 0, 512;\n" ::: "memory");
    if (cta >= NI) {
      uint32_t a[4], d[2][6][2];
#pragma unroll
      for (int j = 0; j < 4; j++) a[j] = swz(sbase + SM_V + j * PLANE + ((tid & 127) >> 3) * 64, lane >> 1) + (lane & 1) * 8;
      const bool bot = y0 == 216;
      uint32_t tsv = 0;
      uint32_t off = 0;
#pragma unroll 1
      for (int u = 0; u < 6; u++) {
        const uint32_t a5 = bot && ((u ^ ry) & 1) ? a[0] : a[1], o34 = u & 1 ? 0 : 4 * PLANE;
        mbar_wait(bars + (B_XF + u) * 8);
        if (VGATE && u >= 1) mbar_wait(bars + (B_XR + u - 1) * 8);
#pragma unroll
        for (int i = 0; i < 4 - VC; i++) {
          v_load(d[0], a, a5, off + i * 1024);
          v_store(d[0], a, 4 * PLANE - o34, o34, off + i * 1024);
        }
        if ((u & 3) == (wid & 3) && lane < 16) {
          const uint32_t h = off + 4096 - (wid & 2) * 256;
          v_load(d[1], a, a5, x0 == 160 && lane >= 8 ? h - 64 : h);
          v_store(d[1], a, 4 * PLANE - o34, o34, h);
        }
        proxy_fence();
        __syncwarp();
        arrive_if(one ? bars + (B_XR + u) * 8 : 0u);
        if (TSBON && lane == u) tsv = clock32() - tstart;
        off += UNIT + ((u ^ wid) & 1 ? -256 : 256);
      }
    }
  } else {
    asm volatile("setmaxnreg.dec.sync.aligned.u32 32;\n");
    const int tid = thread_id(), lane = tid & 31;
    const bool one = elect_one();
    if (wid != 12) {
      if (one) {
        if (cta >= NI) {
          if (wid == 13) {
#pragma unroll
            for (int i = 0; i < 6; i++) mbar_init(bars + (B_XR + i) * 8, 8);
          } else if (wid == 15) {
#pragma unroll
            for (int i = 1; i < 6; i++) mbar_init(bars + (B_XF + i) * 8, 1);
          }
        } else {
#pragma unroll
          for (int i = 0; i < 3; i++) mbar_init(bars + (B_WF + 1 + (wid - 13) * 3 + i) * 8, 1);
          mbar_init(bars + (wid == 13 ? B_WE : B_UR + wid - 14) * 8, wid == 13 ? 8 : 1);
          if (wid < 15) mbar_init(bars + (B_XF + wid - 12) * 8, 1);
        }
        if (wid == 14) {
#pragma unroll
          for (int i = 0; i < 8; i++) mbar_init(bars + (B_ST + i) * 8, 4);
#pragma unroll
          for (int i = B_OF; i <= B_OK; i++) mbar_init(bars + i * 8, i != B_OS ? 1 : cta < NI ? 8 : 2);
          sts64(bars + O_CNT, 0, 0);
          sts64(bars + O_CNT + 8, 0, 0);
        }
        asm volatile("fence.mbarrier_init.release.cluster;\n" ::: "memory");
      }
      asm volatile("bar.arrive 3, 256;\n" ::: "memory");
      asm volatile("bar.sync 0, 512;\n" ::: "memory");
      if (cta >= 48 && cta < NI) {
        if (wid == 15 && one) asm volatile("red.relaxed.gpu.global.add.u32 [%0], 1;\n" ::"l"(scr->ready + 6) : "memory");
      } else {
        uint32_t epoch = 0;
        if (wid < 15) {
          mbar_wait(bars + B_EP * 8);
          epoch = lds32(bars + O_EPO);
        }
        if (cta >= NI && wid < 15) {
          const uint32_t lim = (pack2((float)max(y0, 34) - 1.5f, (float)max(x0, 34) - 1.5f) & 0x7f807f80u) - 0x04000400u;
          uint32_t big = 0;
          mbar_wait(bars + B_OF * 8);
          TSE(6);
#pragma unroll 1
          for (int i0 = 0; i0 < 18; i0 += SCANB) {
            uint32_t v[SCANB][4];
#pragma unroll
            for (int i = 0; i < SCANB; i++) lds128(v[i], sbase + SM_OFF + (tid - 416) * 16 + (i0 + i) * 1024);
#pragma unroll
            for (int i = 0; i < SCANB; i++) {
              const __nv_bfloat162 mx = __hmax2_nan(__hmax2_nan(__habs2(as_bf2(v[i][0])), __habs2(as_bf2(v[i][1]))),
                                                    __hmax2_nan(__habs2(as_bf2(v[i][2])), __habs2(as_bf2(v[i][3]))));
              big = big * 2 + !__hblt2(mx, as_bf2(lim));
            }
          }
#pragma unroll 1
          for (int k = 0; big; k++) {
            const uint32_t wi = (tid - 416 + (18 - __ffs(big)) * 64) * 4 + (k & 3), id = (wi * 7282) >> 16, tap = wi - id * 9;
            const int ki = (tap * 11) >> 5, h = y0 + (id >> 6), w = x0 + (id & 63);
            const uint32_t gp = pack2((float)(h + ki - 1), (float)(w + (int)tap - ki * 3 - 1)), pos = clip2(hadd2(gp, lds32(sbase + SM_OFF + wi * 4)));
            if (pos != hmin2(gp, 0x435f435fu) && h >= 34 && w >= 34) {
              const uint32_t i = count_up(bars + O_CNT);
              if (i >= MAXEX) break;
              sts32(bars + O_LST + i * 4, id | (request(scr, epoch, pos, h, w, tap) << 16));
            }
            if ((k & 3) == 3) big &= big - 1;
          }
          __syncwarp();
          arrive_if(one ? bars + B_OS * 8 : 0u);
        }
        if (wid == 13) {
          uint32_t m[2] = {}, cnt = 0;
          if (cta >= NI ? x0 == 32 || y0 == 32 : g0 == 32) {
#pragma unroll 1
            for (uint32_t spin = 0;; spin++) {
              ld_pair(m, scr->mail[cta] + min(lane, MAXEX));
              const uint32_t have = __ballot_sync(0xffffffffu, m[1] == epoch);
              cnt = __reduce_max_sync(0xffffffffu, lane == MAXEX ? m[0] : 0u);
              if ((have >> MAXEX) && (cnt > MAXEX || !(~have & ((1u << cnt) - 1)))) break;
              if (spin > (1u << 22)) __trap();
            }
          }
          mbar_wait(bars + B_OS * 8);
          TSE(7);
          if (one) asm volatile("red.relaxed.gpu.global.add.u32 [%0], 1;\n" ::"l"(scr->ready + 6) : "memory");
          const uint32_t own = lds32(bars + O_CNT);
          if (own && lane >= cnt) m[0] = lds32(bars + O_LST + ((lane - cnt) & 15) * 4);
          cnt += own;
          if (cnt > MAXEX || __any_sync(0xffffffffu, lane < cnt && m[0] >> 16 == QUEUE)) cnt = FAILED;
          sts32(bars + O_LST + lane * 4, lane < cnt ? m[0] & 511 : 512);
#pragma unroll 1
          for (uint32_t got = 0; got < cnt && cnt != FAILED; got += 4) {
            const uint32_t i = min(got + (lane >> 3), cnt - 1);
            const uint2* r = scr->res[__shfl_sync(0xffffffffu, m[0], i) >> 16] + (lane & 7);
            uint32_t v[12];
#pragma unroll 1
            for (uint32_t spin = 0;; spin++) {
              uint32_t miss = 0;
#pragma unroll
              for (int k = 0; k < 6; k++) ld_pair(v + k * 2, r + k * 8);
#pragma unroll
              for (int k = 0; k < 6; k++) miss |= v[k * 2 + 1] ^ epoch;
              if (__all_sync(0xffffffffu, !miss)) break;
              if (spin > (1u << 22)) __trap();
            }
#pragma unroll
            for (int k = 0; k < 6; k++) sts32(bars + O_COR + i * 192 + (lane & 7) * 4 + k * 32, v[k * 2]);
          }
          if (one) sts32(bars + O_VER, cnt);
          __syncwarp();
          arrive_if(one ? bars + B_OK * 8 : 0u);
          TSE(0);
        } else {
          if (wid == 15) {
            uint32_t epoch = 0, seen = cta < NI ? 0x27 : 0;
            wait_until(tstart, POLLT);
#pragma unroll 1
            for (uint32_t spin = 0; seen != 63; spin++) {
              uint32_t v;
              asm volatile("ld.acquire.gpu.global.u32 %0, [%1];\n" : "=r"(v) : "l"(scr->ready + min(lane, 6)) : "memory");
              if (spin == 0) epoch = (__reduce_max_sync(0xffffffffu, lane == 6 ? v : 0u) & ~127u) + 128;
              const uint32_t now = __ballot_sync(0xffffffffu, v == epoch) & ~seen & 63;
              if (now) {
                asm volatile("fence.proxy.async.global;\n" ::: "memory");
                __syncwarp();
                arrive_if((now >> lane) & 1 ? bars + (B_UR + (cta < NI ? lane - 3 : min(lane, 3))) * 8 : 0u);
                seen |= now;
              }
              if (spin == 0) {
                if (one) sts32(bars + O_EPO, epoch);
                arrive_if(one ? bars + B_EP * 8 : 0u);
              }
              if (spin > (1u << 20)) __trap();
            }
            TSE(4);
          }
          const int t = wid & 1;
          mbar_wait(bars + B_OK * 8);
          const uint32_t cnt = lds32(bars + O_VER);
          if (cnt != FAILED) {
            const uint32_t id = lds32(bars + O_LST + lane * 4);
            mbar_wait(bars + (B_ST + t * 4) * 8);
            if (cta < NI) {
              patch(id, t * 128, 128, sbase + t * 3 * SLOT, 8192, bars, lane);
              if (one) tma_store(&tm.bout[band], sbase + t * 3 * SLOT, g0, t * 16);
            } else {
              const int r0 = ((t ^ ry) & 1) * 4;
#pragma unroll 1
              for (int r = 0; r < 4; r++) {
                const uint32_t base = r < 2 ? sbase + SM_X + (2 + r * 2) * UNIT + t * 21504 : sbase + SM_V + t * (UNIT + 4 * PLANE) + (r - 2) * PLANE;
                const uint32_t pitch = r < 2 ? 4096 : 2 * UNIT;
                const int row = r0 + ((2 - r) & 3);
                if (r >= 2) mbar_wait(bars + (B_ST + t * 4 + r - 1) * 8);
                patch(id, row * 64, 64, base, pitch, bars, lane);
#pragma unroll
                for (int k = 0; k < 3; k++)
                  if (one) tma_store3(&tm.out, base + k * pitch, k * 32, x0, y0 + row);
              }
            }
            if (one) asm volatile("cp.async.bulk.commit_group;\ncp.async.bulk.wait_group.read 0;\n" ::: "memory");
            TSE(2);
          }
        }
      }
    } else if (cta < NI) {
        auto load_x = [&](int s) {
          mbar_expect_tx(bars + (B_XF + s) * 8, YSLICE);
          tma_load_3d(sbase + SM_YX + s * YSLICE, &tm.bx[band], bars + (B_XF + s) * 8, s * 32, g0 - 1, -2);
        };
        auto load_w = [&](int p) {
          const int s = (p * 11) >> 5, b = p - s * 3;
          mbar_expect_tx(bars + (B_WF + p) * 8, 2 * SLOT);
#pragma unroll
          for (int h = 0; h < 2; h++)
            tma_load_5d(sbase + (p * 2 + h) * SLOT, &tm.bw[band], bars + (B_WF + p) * 8, s * 32 + h * 16, band ? 0 : b, band ? b : 0);
        };
        asm volatile("bar.sync 3, 256;\n" ::: "memory");
        if (one && cta >= 48) {
#pragma unroll 1
          for (int sl = 0; sl < 3; sl++) {
            wait_until(tstart, sl * GDT);
#pragma unroll
            for (int wg = 0; wg < 2; wg++) {
              mbar_expect_tx(bars + (B_G + 9 + wg * 3 + sl) * 8, GSLICE);
              tma_load_3d(sbase + SM_GX + (wg * 3 + sl) * GSLICE, &tm.gx, bars + (B_G + 9 + wg * 3 + sl) * 8, sl * 32,
                          (cta & 2) * 4 + ((cta >> 2 ^ wg) & 1) * 16 - 2, (cta & 1) * 8 + wg * 16 - 2);
            }
#pragma unroll 1
            for (int i = 0; i < 6; i++) {
              if (!(i & 1)) mbar_expect_tx(bars + (B_G + sl * 3 + (i >> 1)) * 8, 2 * SLOT);
              tma_load_5d(sbase + (sl * 6 + i) * SLOT, &tm.bw[1], bars + (B_G + sl * 3 + (i >> 1)) * 8, sl * 32 + (i & 1) * 16, 0, i >> 1);
            }
          }
        }
        if (one && cta < 48) {
          arrive_if(bars + (B_WF + 9) * 8);
#pragma unroll 1
          for (int p = 1; p < 9; p++) {
            wait_until(tstart, YWT + (p - 1) * YWDT);
            if (p == YP1) load_x(1);
            if (p == YP2) load_x(2);
            if (p == 8) mbar_wait(bars + B_WE * 8);
            if (p < 3) {
              load_w(p);
            } else {
              const int s = p >= 6 ? 2 : 1, b = p - s * 3;
              mbar_wait(bars + (B_UR + s - 1) * 8);
              mbar_expect_tx(bars + (B_WF + p) * 8, 2 * SLOT);
              if (band) bulk_load<2 * SLOT>(sbase + p * 2 * SLOT, scr->w + (b * 6 + s * 2) * 576, bars + (B_WF + p) * 8);
              else tma_load_5t(sbase + p * 2 * SLOT, &tm.wt, bars + (B_WF + p) * 8, b, s * 2);
            }
          }
        }
    } else {
        auto load_x = [&](int u) {
          mbar_expect_tx(bars + (B_XF + u) * 8, UNIT);
          tma_load_3d(sbase + SM_V + u * UNIT, &tm.x, bars + (B_XF + u) * 8, (u >> 1) * 32, x0 - 1, y0 + ((u ^ ry) & 1) * 4 - 1);
        };
        asm volatile("bar.sync 3, 256;\n" ::: "memory");
        if (lane < 28) mbar_expect_tx(bars + (B_WF + 8 + lane) * 8, lane == 26 ? 2 * SLOT : lane == 27 ? 0 : SLOT);
        if (smem_u32(smem) != sbase) __trap();
#pragma unroll 1
        for (int xu = 1; xu <= XN; xu++) {
          wait_until(tstart, XT1 + (xu - 1) * XDT);
          if (xu == 3) mbar_wait(bars + (B_WF + 4) * 8);
          if (one) load_x(xu);
        }
        const uint4* src = scr->u;
        uint32_t fb = bars + (B_WF + 8) * 8;
#pragma unroll 1
        for (int q = 0; q < 6; q++) {
          mbar_wait(bars + (B_UR + (q < 4 ? min(q, 2) : 3)) * 8);
          if (q == 4) {
            if (one) bulk_load<SLOT>(sbase + SM_X, src, fb);
            if (one) bulk_load<SLOT>(sbase + SM_X + 2 * UNIT + 12288, src + 576, fb + 8);
            src += 2 * 576;
            fb += 16;
          }
          if (q == 5) src += 6 * 576;
          const uint32_t dst = sbase + SM_W + (q & 1) * 4 * SLOT, id = 8 + (q & 1) * 4;
#pragma unroll
          for (int k = 0; k < 4; k++) {
            asm volatile("bar.sync %0, 96;\n" ::"r"(id + k) : "memory");
            if (one) bulk_load<SLOT>(dst + k * SLOT, src + k * 576, fb + k * 8);
          }
          if (q == 1 && one) {
            mbar_expect_tx(bars + B_OF * 8, 2 * SLOT);
            tma_load_3d(sbase + SM_OFF, &tm.off, bars + B_OF * 8, 0, x0 * 9 / 32, y0);
            if (XN < 4) load_x(4);
            if (XN < 5) load_x(5);
          }
          src += 4 * 576;
          fb += 32;
        }
        mbar_wait(bars + B_OS * 8);
        if (one) bulk_load<2 * SLOT>(sbase + SM_OFF, src, fb);
    }
  }
}

typedef CUresult (*EncodeTiledFn)(CUtensorMap*, CUtensorMapDataType, cuuint32_t, void*, const cuuint64_t*,
                                  const cuuint64_t*, const cuuint32_t*, const cuuint32_t*, CUtensorMapInterleave,
                                  CUtensorMapSwizzle, CUtensorMapL2promotion, CUtensorMapFloatOOBfill);

}

extern "C" void kernel_launch(void* const* d_in, const int* in_sizes, int n_in, void* d_out, int out_size) {
  static EncodeTiledFn encode = nullptr;
  static Scratch* scratch = nullptr;
  if (!encode) {
    void* fn = nullptr;
    cudaDriverEntryPointQueryResult qres;
    cudaGetDriverEntryPoint("cuTensorMapEncodeTiled", &fn, cudaEnableDefault, &qres);
    encode = (EncodeTiledFn)fn;
    cudaGetSymbolAddress((void**)&scratch, g_scratch);
    cudaFuncSetAttribute(dcn_kernel, cudaFuncAttributeMaxDynamicSharedMemorySize, SMEM_BYTES);
  }
  uint32_t* tsp = nullptr;
  Maps tm;
  auto make = [&](CUtensorMap* m, void* p, int rank, const cuuint64_t* dims, const cuuint64_t* strides, const cuuint32_t* box, bool swizzle) {
    const cuuint32_t es[5] = {1, 1, 1, 1, 1};
    encode(m, CU_TENSOR_MAP_DATA_TYPE_BFLOAT16, rank, p, dims, strides, box, es, CU_TENSOR_MAP_INTERLEAVE_NONE,
           swizzle ? CU_TENSOR_MAP_SWIZZLE_64B : CU_TENSOR_MAP_SWIZZLE_NONE, CU_TENSOR_MAP_L2_PROMOTION_NONE,
           CU_TENSOR_MAP_FLOAT_OOB_FILL_NONE);
  };
  const cuuint64_t PX = IC * 2, ROW = IW * IC * 2, TAP = IC * IC * 2;
  for (int t = 0; t < 2; t++) {
    const cuuint64_t dims[3] = {IC, IW, IH}, odims[4] = {32, IW, IH, 3}, strides[3] = {t ? ROW : PX, t ? PX : ROW, 64};
    const cuuint32_t xb[3] = {32, 66, 6}, ob[3] = {32, 64, 1}, bxb[3] = {32, 10, 36}, bob[4] = {32, 8, 16, 3};
    if (!t) make(&tm.x, d_in[0], 3, dims, strides, xb, true);
    if (!t) make(&tm.out, d_out, 3, dims, strides, ob, true);
    const cuuint32_t gxb[3] = {32, 12, 12}, gob[4] = {32, 8, 8, 3};
    if (!t) make(&tm.gx, d_in[0], 3, dims, strides, gxb, true);
    if (!t) make(&tm.gout, d_out, 4, odims, strides, gob, true);
    make(&tm.bx[t], d_in[0], 3, dims, strides, bxb, true);
    make(&tm.bout[t], d_out, 4, odims, strides, bob, true);
    const cuuint64_t wdims[5] = {32, IC, 3, 3, 3}, wstrides[4] = {PX, 64, TAP, 3 * TAP};
    const cuuint32_t wb[5] = {32, 16, 3, t ? 3u : 1u, t ? 1u : 3u};
    make(&tm.bw[t], d_in[2], 5, wdims, wstrides, wb, true);
  }
  {
    const cuuint64_t dims[3] = {64, 144, 9}, strides[2] = {128, TAP};
    const cuuint32_t box[3] = {64, 48, 9};
    make(&tm.w, d_in[2], 3, dims, strides, box, false);
    const cuuint64_t cdims[4] = {64, 144, 3, 3}, cstrides[3] = {128, TAP, 3 * TAP};
    const cuuint32_t cbox[4] = {64, 24, 1, 3};
    make(&tm.wc, d_in[2], 4, cdims, cstrides, cbox, false);
    const cuuint64_t odims[3] = {64, 63, IH}, ostrides[2] = {128, IW * 36};
    const cuuint32_t obox[3] = {64, 18, 8};
    make(&tm.off, d_in[1], 3, odims, ostrides, obox, false);
    const cuuint32_t cb[3] = {64, 1, IH};
    make(&tm.col, d_in[1], 3, odims, ostrides, cb, false);
    const cuuint64_t tdims[5] = {64, 24, 3, 3, 6}, tstrides[4] = {128, 3072, 6 * SLOT, SLOT};
    const cuuint32_t tbox[5] = {64, 24, 1, 3, 2};
    make(&tm.wt, scratch->w, 5, tdims, tstrides, tbox, false);
  }
  dcn_kernel<<<GRID, NTHREADS, SMEM_BYTES>>>((const uint4*)d_in[0], (const uint32_t*)d_in[1], (const uint4*)d_in[2], scratch, tsp, 0u, tm);
}
```

```cpp
#include <cuda_runtime.h>
#include <cuda.h>
#include <cuda_bf16.h>
#include <stdint.h>

namespace {

constexpr int IH = 224, IW = 224, IC = 96;
constexpr int GRID = 132, NTHREADS = 512;
constexpr int NI = 60, NR = GRID - NI;
constexpr int SLOT = 9216;
constexpr int SMEM_BYTES = 232448;
constexpr int PLANE = 66 * 64, UNIT = 6 * PLANE;
constexpr int SM_V = 256, SM_X = 8704, SM_W = 36 * PLANE + 512, SM_BAR = SM_W + 8 * SLOT;
constexpr int B_WF = 0, B_WE = 36, B_XF = 60, B_XR = 66, B_ST = 72, B_UR = 80, B_OF = 84, B_OS = 85, B_EP = 86, B_OK = 87, B_G = 88;
constexpr int O_CNT = 832, O_VER = 848, O_EPO = 852, O_LST = 864, O_COR = 1024;
constexpr int MAXEX = 16, EARLY = 128, QUEUE = 192;
constexpr uint32_t FAILED = 255;
constexpr int GSLICE = 144 * 64, SM_GX = 18 * SLOT;
constexpr int SM_RAW = SM_V + 3 * UNIT, SM_OFF = SM_V + 6 * UNIT - 2 * SLOT;
constexpr int YSLICE = 36 * 10 * 64, SM_YX = 16 * SLOT, SM_YT = SM_YX + 3 * YSLICE;
#define PSLEEP 20
#define REDSEM "red.release"
#define XN 3
#define XJ4 3
#define XJ5 7
#define HAND 12
#define PUB1 10
#define TGRP 8
#define TDEP 0
#define TSBON 0
#define YPRMT 1
#define STW 0
#define LATE4 0
#define PW -1
#define TX 0
#define SPACE 2
#define VC 2
#define VGATE 0
#define YLAG 0
#define KEEP 0
#define YP1 3
#define YP2 6
#define MIX 1
#define YORD 1
#define Y0M 0
#define POLLT 4700
#define TS2 1
#define T2N 2
#define PUB0 3
#define GDT 3000
#define SCANB 3
#define OFFAT 3
#define UHOLD 1
#define USTG 1
#define FWT 0
#define EWAIT 1
#define PFLY 1
#define PGAP 150
#define X5W 12
#define WAT 0
#define R2 32
#define XT1 1900
#define XT2 3800
#define XDT 900
#define YX0 900
#define YX1 5000
#define YX2 8500
#define YWT 2500
#define YWDT 1100

struct Scratch {
  uint4 u[16 * SLOT / 16];
  uint4 w[12 * SLOT / 16];
  uint32_t ready[32];
  uint2 req[QUEUE];
  uint2 res[QUEUE][48];
  uint2 mail[GRID][32];
};
__device__ __align__(128) Scratch g_scratch;

#define TSE(i)
#define TSB(i)

__device__ __forceinline__ float bf16lo(uint32_t v) { return __uint_as_float(v << 16); }
__device__ __forceinline__ float bf16hi(uint32_t v) { return __uint_as_float(v & 0xffff0000u); }
__device__ __forceinline__ uint32_t smem_u32(const void* p) { return (uint32_t)__cvta_generic_to_shared(p); }
__device__ __forceinline__ void mbar_init(uint32_t bar, uint32_t count) {
  asm volatile("mbarrier.init.shared::cta.b64 [%0], %1;\n" ::"r"(bar), "r"(count) : "memory");
}
__device__ __forceinline__ void mbar_expect_tx(uint32_t bar, uint32_t bytes) {
  asm volatile("mbarrier.arrive.expect_tx.shared::cta.b64 _, [%0], %1;\n" ::"r"(bar), "r"(bytes) : "memory");
}
__device__ __forceinline__ void mbar_wait(uint32_t bar, uint32_t parity = 0) {
  uint32_t done;
#pragma unroll 1
  for (uint32_t spin = 0; spin < (1u << 22); spin++) {
    asm volatile(
        "{\n.reg .pred p;\n"
        "mbarrier.try_wait.parity.shared::cta.b64 p, [%1], %2;\n"
        "selp.u32 %0, 1, 0, p;\n}\n"
        : "=r"(done)
        : "r"(bar), "r"(parity)
        : "memory");
    if (done) return;
  }
  __trap();
}
__device__ __forceinline__ uint32_t mbar_test(uint32_t bar, uint32_t parity = 0) {
  uint32_t done;
  asm volatile(
      "{\n.reg .pred p;\n"
      "mbarrier.test_wait.parity.shared::cta.b64 p, [%1], %2;\n"
      "selp.u32 %0, 1, 0, p;\n}\n"
      : "=r"(done)
      : "r"(bar), "r"(parity)
      : "memory");
  return done;
}
__device__ __forceinline__ uint32_t clock32() {
  uint32_t c;
  asm volatile("mov.u32 %0, %%clock;\n" : "=r"(c)::"memory");
  return c;
}
__device__ __forceinline__ void wait_until(uint32_t t0, uint32_t dt) {
  while (clock32() - t0 < dt) __nanosleep(50);
}
__device__ __forceinline__ void mbar_wait_cluster(uint32_t bar, uint32_t parity = 0) {
  uint32_t done;
#pragma unroll 1
  for (uint32_t spin = 0; spin < (1u << 22); spin++) {
    asm volatile(
        "{\n.reg .pred p;\n"
        "mbarrier.try_wait.parity.acquire.cluster.shared::cta.b64 p, [%1], %2;\n"
        "selp.u32 %0, 1, 0, p;\n}\n"
        : "=r"(done)
        : "r"(bar), "r"(parity)
        : "memory");
    if (done) return;
  }
  __trap();
}
__device__ __forceinline__ void tma_load_3d(uint32_t dst, const CUtensorMap* tm, uint32_t bar, int c0, int c1, int c2) {
  asm volatile(
      "cp.async.bulk.tensor.3d.shared::cluster.global.mbarrier::complete_tx::bytes [%0], [%1, {%3, %4, %5}], [%2];\n" ::"r"(dst),
      "l"(reinterpret_cast<uint64_t>(tm)), "r"(bar), "r"(c0), "r"(c1), "r"(c2)
      : "memory");
}
__device__ __forceinline__ void tma_load_5d(uint32_t dst, const CUtensorMap* tm, uint32_t bar, int c, int kj, int ki) {
  asm volatile(
      "cp.async.bulk.tensor.5d.shared::cluster.global.mbarrier::complete_tx::bytes [%0], [%1, {%3, %4, %3, %5, %6}], [%2];\n" ::"r"(dst),
      "l"(reinterpret_cast<uint64_t>(tm)), "r"(bar), "r"(0), "r"(c), "r"(kj), "r"(ki)
      : "memory");
}
__device__ __forceinline__ void tma_load_4d(uint32_t dst, const CUtensorMap* tm, uint32_t bar, int c1, int c2, int c3) {
  asm volatile(
      "cp.async.bulk.tensor.4d.shared::cluster.global.mbarrier::complete_tx::bytes [%0], [%1, {%3, %4, %5, %6}], [%2];\n" ::"r"(dst),
      "l"(reinterpret_cast<uint64_t>(tm)), "r"(bar), "r"(0), "r"(c1), "r"(c2), "r"(c3)
      : "memory");
}
__device__ __forceinline__ void tma_load_5t(uint32_t dst, const CUtensorMap* tm, uint32_t bar, int kj, int chunk) {
  asm volatile(
      "cp.async.bulk.tensor.5d.shared::cluster.global.mbarrier::complete_tx::bytes [%0], [%1, {%3, %3, %4, %3, %5}], [%2];\n" ::"r"(dst),
      "l"(reinterpret_cast<uint64_t>(tm)), "r"(bar), "r"(0), "r"(kj), "r"(chunk)
      : "memory");
}
template <int BYTES>
__device__ __forceinline__ void bulk_load(uint32_t dst, const void* src, uint32_t bar) {
  asm volatile("cp.async.bulk.shared::cluster.global.mbarrier::complete_tx::bytes [%0], [%1], %3, [%2];\n" ::"r"(dst), "l"(src),
               "r"(bar), "n"(BYTES)
               : "memory");
}
template <int BYTES>
__device__ __forceinline__ void bulk_store(void* dst, uint32_t src) {
  asm volatile("cp.async.bulk.global.shared::cta.bulk_group [%0], [%1], %2;\n" ::"l"(dst), "r"(src), "n"(BYTES) : "memory");
}
__device__ __forceinline__ void tma_store3(const CUtensorMap* tm, uint32_t src, int c0, int c1, int c2) {
  asm volatile("cp.async.bulk.tensor.3d.global.shared::cta.bulk_group [%0, {%2, %3, %4}], [%1];\n" ::"l"(
                   reinterpret_cast<uint64_t>(tm)),
               "r"(src), "r"(c0), "r"(c1), "r"(c2)
               : "memory");
}
__device__ __forceinline__ void tma_store(const CUtensorMap* tm, uint32_t src, int c1, int c2) {
  asm volatile("cp.async.bulk.tensor.4d.global.shared::cta.bulk_group [%0, {%2, %3, %4, %2}], [%1];\n" ::"l"(
                   reinterpret_cast<uint64_t>(tm)),
               "r"(src), "r"(0), "r"(c1), "r"(c2)
               : "memory");
}
__device__ __forceinline__ uint64_t w_desc(uint32_t saddr) {
  return (uint64_t)((saddr & 0x3FFFF) >> 4) | ((uint64_t)(1024 >> 4) << 16) | ((uint64_t)(512 >> 4) << 32) | ((uint64_t)2 << 62);
}
__device__ __forceinline__ uint64_t a_desc(uint32_t saddr) {
  return (uint64_t)((saddr & 0x3FFFF) >> 4) | ((uint64_t)1 << 16) | ((uint64_t)(512 >> 4) << 32) | ((uint64_t)2 << 62);
}
#define ACC_OPERANDS(c, d)                                                                                        \
  c(d[0]), c(d[1]), c(d[2]), c(d[3]), c(d[4]), c(d[5]), c(d[6]), c(d[7]), c(d[8]),      \
      c(d[9]), c(d[10]), c(d[11]), c(d[12]), c(d[13]), c(d[14]), c(d[15]), c(d[16]),       \
      c(d[17]), c(d[18]), c(d[19]), c(d[20]), c(d[21]), c(d[22]), c(d[23]), c(d[24]),      \
      c(d[25]), c(d[26]), c(d[27]), c(d[28]), c(d[29]), c(d[30]), c(d[31]), c(d[32]),      \
      c(d[33]), c(d[34]), c(d[35]), c(d[36]), c(d[37]), c(d[38]), c(d[39]), c(d[40]),      \
      c(d[41]), c(d[42]), c(d[43]), c(d[44]), c(d[45]), c(d[46]), c(d[47])
#define ACC_LIST                                                                   \
  "{%0, %1, %2, %3, %4, %5, %6, %7, %8, %9, %10, %11, %12, %13, %14, %15, "        \
  "%16, %17, %18, %19, %20, %21, %22, %23, %24, %25, %26, %27, %28, %29, %30, %31, " \
  "%32, %33, %34, %35, %36, %37, %38, %39, %40, %41, %42, %43, %44, %45, %46, %47}, "
__device__ __forceinline__ void wgmma_ss(float* d, uint64_t adesc, uint64_t bdesc, int accumulate = 1) {
  asm volatile(
      "{\n.reg .pred p;\nsetp.ne.b32 p, %50, 0;\n"
      "wgmma.mma_async.sync.aligned.m64n96k16.f32.bf16.bf16 " ACC_LIST "%48, %49, p, 1, 1, 0, 1;\n}\n"
      : ACC_OPERANDS("+f", d)
      : "l"(adesc), "l"(bdesc), "r"(accumulate));
}
__device__ __forceinline__ void wgmma_fence() { asm volatile("wgmma.fence.sync.aligned;\n" ::: "memory"); }
__device__ __forceinline__ void wgmma_commit() { asm volatile("wgmma.commit_group.sync.aligned;\n" ::: "memory"); }
template <int N>
__device__ __forceinline__ void wgmma_wait() { asm volatile("wgmma.wait_group.sync.aligned %0;\n" ::"n"(N) : "memory"); }
__device__ __forceinline__ void acc_fence(float* d) {
#pragma unroll
  for (int i = 0; i < 48; i++) asm volatile("" : "+f"(d[i])::"memory");
}
__device__ __forceinline__ void arrive_if(uint32_t bar) {
  asm volatile("{\n.reg .pred p;\nsetp.ne.u32 p, %0, 0;\n@p mbarrier.arrive.shared::cluster.b64 _, [%0];\n}\n" ::"r"(bar) : "memory");
}
__device__ __forceinline__ void lds128(uint32_t* v, uint32_t addr) {
  asm volatile("ld.shared.v4.b32 {%0, %1, %2, %3}, [%4];\n" : "=r"(v[0]), "=r"(v[1]), "=r"(v[2]), "=r"(v[3]) : "r"(addr) : "memory");
}
__device__ __forceinline__ void sts128(uint32_t addr, const uint32_t* v) {
  asm volatile("st.shared.v4.b32 [%0], {%1, %2, %3, %4};\n" ::"r"(addr), "r"(v[0]), "r"(v[1]), "r"(v[2]), "r"(v[3]) : "memory");
}
__device__ __forceinline__ __nv_bfloat162 as_bf2(uint32_t v) { return *reinterpret_cast<__nv_bfloat162*>(&v); }
__device__ __forceinline__ uint32_t as_u32(__nv_bfloat162 v) { return *reinterpret_cast<uint32_t*>(&v); }
__device__ __forceinline__ uint32_t hfma2(uint32_t a, uint32_t b, uint32_t c) { return as_u32(__hfma2(as_bf2(a), as_bf2(b), as_bf2(c))); }
__device__ __forceinline__ uint32_t pack2(float a, float b) { return as_u32(__floats2bfloat162_rn(a, b)); }
__device__ __forceinline__ bool elect_one() {
  uint32_t r;
  asm volatile("{\n.reg .pred p;\nelect.sync _|p, 0xffffffff;\nselp.u32 %0, 1, 0, p;\n}\n" : "=r"(r));
  return r != 0;
}
__device__ __forceinline__ void wgmma_rs(float* d, const uint32_t* a, uint64_t bdesc, int accumulate = 1) {
  asm volatile(
      "{\n.reg .pred p;\nsetp.ne.b32 p, %53, 0;\n"
      "wgmma.mma_async.sync.aligned.m64n96k16.f32.bf16.bf16 " ACC_LIST "{%48, %49, %50, %51}, %52, p, 1, 1, 1;\n}\n"
      : ACC_OPERANDS("+f", d)
      : "r"(a[0]), "r"(a[1]), "r"(a[2]), "r"(a[3]), "l"(bdesc), "r"(accumulate));
}
__device__ __forceinline__ void ldsm4(uint32_t* r, uint32_t addr) {
  asm volatile("ldmatrix.sync.aligned.m8n8.x4.shared.b16 {%0, %1, %2, %3}, [%4];\n"
               : "=r"(r[0]), "=r"(r[1]), "=r"(r[2]), "=r"(r[3])
               : "r"(addr)
               : "memory");
}
__device__ __forceinline__ void lds64(uint32_t* v, uint32_t addr) {
  asm volatile("ld.shared.v2.b32 {%0, %1}, [%2];\n" : "=r"(v[0]), "=r"(v[1]) : "r"(addr) : "memory");
}
__device__ __forceinline__ void sts64(uint32_t addr, uint32_t a, uint32_t b) {
  asm volatile("st.shared.v2.b32 [%0], {%1, %2};\n" ::"r"(addr), "r"(a), "r"(b) : "memory");
}
__device__ __forceinline__ void sts32(uint32_t addr, uint32_t v) {
  asm volatile("st.shared.u32 [%0], %1;\n" ::"r"(addr), "r"(v) : "memory");
}
__device__ __forceinline__ uint32_t hadd2(uint32_t a, uint32_t b) { return as_u32(__hadd2(as_bf2(a), as_bf2(b))); }
__device__ __forceinline__ uint32_t hsub2(uint32_t a, uint32_t b) { return as_u32(__hsub2(as_bf2(a), as_bf2(b))); }
__device__ __forceinline__ uint32_t hmin2(uint32_t a, uint32_t b) { return as_u32(__hmin2(as_bf2(a), as_bf2(b))); }
__device__ __forceinline__ uint32_t hmax2(uint32_t a, uint32_t b) { return as_u32(__hmax2(as_bf2(a), as_bf2(b))); }
__device__ __forceinline__ uint32_t hfma2_lo(uint32_t w, uint32_t a, uint32_t c) {
  return as_u32(__hfma2(__low2bfloat162(as_bf2(w)), as_bf2(a), as_bf2(c)));
}
__device__ __forceinline__ uint32_t hfma2_hi(uint32_t w, uint32_t a, uint32_t c) {
  return as_u32(__hfma2(__high2bfloat162(as_bf2(w)), as_bf2(a), as_bf2(c)));
}
__device__ __forceinline__ uint32_t prmt(uint32_t a, uint32_t b, uint32_t sel) {
  uint32_t r;
  asm("prmt.b32 %0, %1, %2, %3;\n" : "=r"(r) : "r"(a), "r"(b), "r"(sel));
  return r;
}
__device__ __forceinline__ constexpr uint32_t tap_delta(int a, int b) {
  return (a == 0 ? 0xbf80u : a == 1 ? 0u : 0x3f80u) | (b == 0 ? 0xbf800000u : b == 1 ? 0u : 0x3f800000u);
}
__device__ __forceinline__ int thread_id() {
  int t;
  asm volatile("mov.u32 %0, %%tid.x;\n" : "=r"(t));
  return t;
}
__device__ __forceinline__ void proxy_fence() { asm volatile("fence.proxy.async.shared::cta;\n" ::: "memory"); }
template <int PITCH>
__device__ __forceinline__ void stage16(const float* acc, int jp, uint32_t stg) {
  uint32_t pk[4];
#pragma unroll
  for (int i = 0; i < 4; i++) pk[i] = pack2(acc[jp * 8 + i * 2], acc[jp * 8 + i * 2 + 1]);
  asm volatile("stmatrix.sync.aligned.m8n8.x4.shared.b16 [%0], {%1, %2, %3, %4};\n" ::"r"((stg ^ ((jp & 1) * 32)) + (jp >> 1) * PITCH),
               "r"(pk[0]), "r"(pk[1]), "r"(pk[2]), "r"(pk[3])
               : "memory");
}
__device__ __forceinline__ uint32_t swz(uint32_t a, uint32_t chunk) { return a | (((chunk ^ (a >> 7)) & 3) << 4); }
__device__ __forceinline__ void fma_ip(float& d, float c, float a) { asm volatile("fma.rn.f32 %0, %1, %2, %0;\n" : "+f"(d) : "f"(c), "f"(a)); }
__device__ __forceinline__ void fma_sc(float& d, float c, float a) { asm volatile("fma.rn.f32 %0, %1, %0, %2;\n" : "+f"(d) : "f"(c), "f"(a)); }

__device__ __forceinline__ void v_load(uint32_t (*d)[2], const uint32_t* a, uint32_t a5, uint32_t off) {
#pragma unroll
  for (int j = 0; j < 6; j++) lds64(d[j], (j == 5 ? a5 : a[j & 3]) + (j >> 2) * 4 * PLANE + off);
}
__device__ __forceinline__ void v_store(uint32_t (*d)[2], const uint32_t* a, uint32_t o05, uint32_t o34, uint32_t off) {
#pragma unroll
  for (int i = 0; i < 2; i++)
    asm volatile(
        "{\n.reg .b32 p, q, r, c;\n"
        "add.rn.bf16x2 %0, %0, %4;\n"
        "add.rn.bf16x2 %5, %5, %1;\n"
        "mov.b32 c, 0xc080c080;\n"
        "fma.rn.bf16x2 p, c, %2, %4;\n"
        "fma.rn.bf16x2 q, c, %1, %3;\n"
        "mov.b32 c, 0xc088c088;\n"
        "fma.rn.bf16x2 %0, c, %2, %0;\n"
        "fma.rn.bf16x2 %5, c, %3, %5;\n"
        "mov.b32 c, 0xbe80be80;\n"
        "fma.rn.bf16x2 r, c, %2, %4;\n"
        "fma.rn.bf16x2 %3, c, %1, %3;\n"
        "mov.b32 c, 0x3f003f00;\n"
        "fma.rn.bf16x2 %1, c, q, p;\n"
        "mov.b32 c, 0xbf00bf00;\n"
        "fma.rn.bf16x2 %2, c, q, p;\n"
        "mov.b32 c, 0x40004000;\n"
        "fma.rn.bf16x2 %4, c, %3, r;\n"
        "mov.b32 c, 0xc000c000;\n"
        "fma.rn.bf16x2 %3, c, %3, r;\n}\n"
        : "+r"(d[0][i]), "+r"(d[1][i]), "+r"(d[2][i]), "+r"(d[3][i]), "+r"(d[4][i]), "+r"(d[5][i]));
  sts64(a[0] + o05 + off, d[0][0], d[0][1]);
  sts64(a[1] + o05 + off, d[5][0], d[5][1]);
  sts64(a[2] + off, d[1][0], d[1][1]);
  sts64(a[3] + off, d[2][0], d[2][1]);
  sts64(a[0] + o34 + off, d[4][0], d[4][1]);
  sts64(a[1] + o34 + off, d[3][0], d[3][1]);
}
__device__ __forceinline__ void u_math16(const uint32_t (*g)[4], uint32_t dst) {
  uint32_t u[4][4];
#pragma unroll
  for (int i = 0; i < 4; i++) {
    const uint32_t s = hfma2(0x3e803e80u, g[2][i], g[0][i]), t = hfma2(0x3e803e80u, g[0][i], g[2][i]);
    u[0][i] = hfma2(0x3f003f00u, g[1][i], s);
    u[1][i] = hfma2(0xbf00bf00u, g[1][i], s);
    u[2][i] = hfma2(0x3f003f00u, g[1][i], t);
    u[3][i] = hfma2(0xbf00bf00u, g[1][i], t);
  }
#pragma unroll
  for (int k = 0; k < 4; k++) sts128(dst + k * SLOT, u[k]);
}

__device__ __forceinline__ void ldg128(uint32_t* v, const uint4* p) {
  asm volatile("ld.global.nc.v4.b32 {%0, %1, %2, %3}, [%4];\n" : "=r"(v[0]), "=r"(v[1]), "=r"(v[2]), "=r"(v[3]) : "l"(p));
}
__device__ __forceinline__ uint32_t lds32(uint32_t addr) {
  uint32_t v;
  asm volatile("ld.shared.u32 %0, [%1];\n" : "=r"(v) : "r"(addr) : "memory");
  return v;
}
__device__ __forceinline__ void ldsm4_if(uint32_t* r, uint32_t addr, uint32_t on) {
  asm volatile(
      "{\n.reg .pred p;\nsetp.ne.u32 p, %5, 0;\n"
      "@p ldmatrix.sync.aligned.m8n8.x4.shared.b16 {%0, %1, %2, %3}, [%4];\n}\n"
      : "+r"(r[0]), "+r"(r[1]), "+r"(r[2]), "+r"(r[3])
      : "r"(addr), "r"(on)
      : "memory");
}
__device__ __forceinline__ uint32_t hmul2_lo(uint32_t w, uint32_t a) { return as_u32(__hmul2(__low2bfloat162(as_bf2(w)), as_bf2(a))); }
__device__ __forceinline__ uint32_t clip2(uint32_t p) { return hmin2(hmax2(p, 0u), 0x435f435fu); }
__device__ __forceinline__ uint32_t frac2(uint32_t pos) {
  const float py = bf16lo(pos), px = bf16hi(pos);
  return __byte_perm(__float_as_uint(py - floorf(py)), __float_as_uint(px - floorf(px)), 0x7632);
}
__device__ __forceinline__ void coefs(uint32_t w, uint32_t& p0, uint32_t& p1) {
  const uint32_t o = hsub2(0x3f803f80u, w), xa = __byte_perm(o, w, 0x7632);
  p0 = hmul2_lo(o, xa);
  p1 = hmul2_lo(w, xa);
}
__device__ __forceinline__ uint32_t blend(uint32_t p0, uint32_t p1, uint32_t t, uint32_t g, uint32_t h, uint32_t k) {
  return hfma2_hi(p1, k, hfma2_lo(p1, h, hfma2_hi(p0, g, hmul2_lo(p0, t))));
}
__device__ __forceinline__ void st_pair(uint2* p, uint32_t a, uint32_t b) {
  asm volatile("st.relaxed.gpu.global.v2.u32 [%0], {%1, %2};\n" ::"l"(p), "r"(a), "r"(b) : "memory");
}
__device__ __forceinline__ void ld_pair(uint32_t* v, const uint2* p) {
  asm volatile("ld.relaxed.gpu.global.v2.u32 {%0, %1}, [%2];\n" : "=r"(v[0]), "=r"(v[1]) : "l"(p) : "memory");
}
__device__ __forceinline__ uint32_t request(Scratch* scr, uint32_t slot, uint32_t pos, int h, int w, int tap) {
  if (slot < QUEUE) st_pair(scr->req + slot, pos, 0x80000000u | (h << 12) | (w << 4) | tap);
  return slot;
}
__device__ __forceinline__ uint32_t count_up(uint32_t addr) {
  uint32_t i;
  asm volatile("atom.shared.add.u32 %0, [%1], 1;\n" : "=r"(i) : "r"(addr) : "memory");
  return i;
}
__device__ __forceinline__ void patch(uint32_t id, uint32_t id0, uint32_t n, uint32_t base, uint32_t pitch, uint32_t ctl, int lane) {
  uint32_t todo = __ballot_sync(0xffffffffu, id - id0 < n);
  if (!todo) return;
#pragma unroll 1
  do {
    const int i0 = __ffs(todo) - 1;
    todo &= todo - 1;
    const uint32_t p0 = __shfl_sync(0xffffffffu, id, i0), other = todo & __ballot_sync(0xffffffffu, id != p0);
    const int i1 = __ffs(other) - 1;
    todo &= ~(other & -other);
    const uint32_t p1 = __shfl_sync(0xffffffffu, id, i1);
    if ((lane & 15) < 12 && (lane < 16 || other)) {
      const uint32_t a = swz(base + ((lane >> 2) & 3) * pitch + ((lane < 16 ? p0 : p1) - id0) * 64, lane);
      uint32_t v[4], c[4];
      lds128(v, a);
      lds128(c, ctl + O_COR + (lane < 16 ? i0 : i1) * 192 + (lane & 15) * 16);
#pragma unroll
      for (int k = 0; k < 4; k++) v[k] = hadd2(v[k], c[k]);
      sts128(a, v);
    }
    __syncwarp();
  } while (todo);
  proxy_fence();
  __syncwarp();
}

struct Maps {
  CUtensorMap x, w, wc, out, off, col, gx, gout;
  CUtensorMap bx[2], bw[2], bout[2];
};

__global__ void __launch_bounds__(NTHREADS, 1)
dcn_kernel(const uint4* __restrict__ x, const uint32_t* __restrict__ offs, const uint4* __restrict__ wgt, Scratch* __restrict__ scr, uint32_t* tsp, const uint32_t never,
           const __grid_constant__ Maps tm) {
  extern __shared__ __align__(1024) uint8_t smem[];
  constexpr uint32_t sbase = 1024;
  constexpr uint32_t bars = sbase + SM_BAR;
  const int tid = threadIdx.x;
  const int bk = blockIdx.x >> 1;
  const int cta = MIX ? (blockIdx.x & 1 ? (bk < 4 ? bk + 56 : bk < 60 ? bk - 4 : bk + 66) : bk + 60) : blockIdx.x;
  const uint32_t tstart = clock32();
  const int wid = __shfl_sync(0xffffffffu, tid >> 5, 0);
  const int lane = tid & 31;
  const int ri = cta - NI, ry = ri / 3, x0 = 32 + (ri - ry * 3) * 64, y0 = 32 + ry * 8;
  const int band = cta >= 24, g0 = 32 + (cta - band * 24) * 8;
  if (wid == 12 && cta >= NI) {
    if (elect_one()) {
      mbar_init(bars + (B_WF + 1) * 8, 1);
      mbar_init(bars + B_XF * 8, 1);
      asm volatile("fence.mbarrier_init.release.cluster;\n" ::: "memory");
      mbar_expect_tx(bars + (B_WF + 1) * 8, 6 * SLOT);
      mbar_expect_tx(bars + B_XF * 8, UNIT);
      tma_load_3d(sbase + SM_RAW, &tm.w, bars + (B_WF + 1) * 8, 0, 0, 0);
      tma_load_3d(sbase + SM_V, &tm.x, bars + B_XF * 8, 0, x0 - 1, y0 + (ry & 1) * 4 - 1);
    }
    asm volatile("bar.arrive 0, 512;\n" ::: "memory");
  }
  if (wid == 12 && cta < NI - 4) {
    if (elect_one() && cta < 48) {
      mbar_init(bars + B_WF * 8, 1);
      mbar_init(bars + B_XF * 8, 1);
      asm volatile("fence.mbarrier_init.release.cluster;\n" ::: "memory");
      mbar_expect_tx(bars + B_WF * 8, 2 * SLOT);
      mbar_expect_tx(bars + B_XF * 8, YSLICE);
      while (clock32() - tstart < YX0) {}
      if (YORD) tma_load_3d(sbase + SM_YX, &tm.bx[band], bars + B_XF * 8, 0, g0 - 1, -2);
      tma_load_5d(sbase, &tm.bw[band], bars + B_WF * 8, 0, 0, 0);
      tma_load_5d(sbase + SLOT, &tm.bw[band], bars + B_WF * 8, 16, 0, 0);
      if (!YORD) tma_load_3d(sbase + SM_YX, &tm.bx[band], bars + B_XF * 8, 0, g0 - 1, -2);
    }
    asm volatile("bar.arrive 0, 512;\n" ::: "memory");
  }
  if (wid == 12 && cta >= NI - 4 && cta < NI) {
    if (elect_one()) {
#pragma unroll
      for (int c = 0; c < 5; c++) mbar_init(bars + c * 8, 1);
      asm volatile("fence.mbarrier_init.release.cluster;\n" ::: "memory");
      if (cta < NI - 1) {
#pragma unroll
        for (int c = 0; c < 4; c++) {
          mbar_expect_tx(bars + c * 8, SLOT);
          tma_load_4d(sbase + (18 + c) * SLOT, &tm.wc, bars + c * 8, (c + 2) * 24, cta - (NI - 4), 0);
        }
      } else {
        mbar_expect_tx(bars + 3 * 8, 28672 + 16128);
        tma_load_3d(sbase + 18 * SLOT, &tm.col, bars + 3 * 8, 0, 9, 0);
        bulk_load<16128>(sbase + 18 * SLOT + 28672, offs + 32 * IW * 9, bars + 3 * 8);

      }
    }
  }
  const int f = wid * 4 + (lane >> 3), g = g0 + (lane & 7);
  uint32_t o9[9];
  if (cta < 48 && wid < 8) {
    const uint32_t* op = offs + (band ? g * IW + f : f * IW + g) * 9;
#pragma unroll
    for (int a = 0; a < 3; a++)
#pragma unroll
      for (int b = 0; b < 3; b++) o9[a * 3 + b] = __ldg(op + (band ? b * 3 + a : a * 3 + b));
  }
  if (cta >= 48 && cta < NI - 4 && tid < 36) asm volatile("prefetch.global.L2 [%0];\n" ::"l"(offs + ((cta & 7) * 4 + tid / 9) * IW * 9 + tid % 9 * 32));
  if (cta >= NI - 4 && cta < NI) {
    const int kj = cta - (NI - 4);
    if (tid < GRID) sts32(bars + 64 + tid * 4, 0);
    __syncthreads();
    uint32_t epoch;
    asm volatile("ld.relaxed.gpu.global.u32 %0, [%1];\n" : "=r"(epoch) : "l"(scr->ready + (kj == 3 ? 3 : 2)) : "memory");
    epoch = (epoch & ~127u) + 128;
    auto load_w = [&]() {
      mbar_expect_tx(bars + 4 * 8, 18 * SLOT);
#pragma unroll
      for (int sl = 0; sl < 3; sl++) tma_load_3d(sbase + sl * 6 * SLOT, &tm.w, bars + 4 * 8, 0, sl * 48, 0);
    };
    if (kj == 3) {
      constexpr uint32_t src = sbase + 18 * SLOT, lst = src + 28672 + 16128;
      uint32_t big = 0;
      if (tid == 0) load_w();
      mbar_wait(bars + 3 * 8);
#pragma unroll
      for (int i = 0; i < 6; i++) {
        const uint32_t p = tid + i * 512;
        uint32_t v[4];
        lds128(v, src + p * 16);
        const uint32_t lim = i == 0 && tid < 256 ? 0x42804080u : i >= 3 && (p - 1792 < 72 || p - 2296 < 72) ? 0x40804280u : 0x42804280u;
        uint32_t over = 0;
#pragma unroll
        for (int k = 0; k < 4; k++) over |= (v[k] & 0x7fff7fffu) + lim;
        if ((over & 0x80008000u) && (p < 1792 ? (tid & 7) < 5 : p < 2800)) big |= 1u << i;
      }
#pragma unroll 1
      for (; big; big &= big - 1) {
        const uint32_t i = count_up(bars + 64 + 57 * 4);
        if (i < 1024) sts32(lst + i * 4, tid + (__ffs(big) - 1) * 512);
      }
      __syncthreads();
      const uint32_t n = lds32(bars + 64 + 57 * 4);
      if (n > 1024 && tid < GRID && (tid < 56 || tid >= NI)) sts32(bars + 64 + tid * 4, FAILED);
#pragma unroll 1
      for (uint32_t c = tid; c < n * 4 && n <= 1024; c += 512) {
        const uint32_t wq = lds32(lst + (c & ~3u)) * 4 + (c & 3), col = wq < 7168;
        const uint32_t wi = col ? wq & 31 : wq - 7168, px = (wi * 7282) >> 16, tap = wi - px * 9;
        const int eh = col ? wq >> 5 : 32 + (px >= 224), ew = col ? 32 + px : px >= 224 ? px - 224 : px, ki = (tap * 11) >> 5;
        const uint32_t gp = pack2((float)(eh + ki - 1), (float)(ew + (int)tap - ki * 3 - 1));
        const uint32_t pos = clip2(hadd2(gp, lds32(src + wq * 4)));
        const uint32_t d = __byte_perm(hsub2(pos, hmin2(gp, 0x435f435fu)), 0, ew < 32 ? 0x1032 : 0x3210) & 0x7fff7fffu;
        if (d <= (min(eh, ew) < 32 ? 0x3f80u : 0u) || (col && (px >= 2 || eh >> 1 == 16))) continue;
        const int client = eh < 32 ? 0 : ew < 32 ? 24 : NI + ((eh - 32) >> 3) * 3 + ((ew - 32) >> 6);
        const uint32_t i = count_up(bars + 64 + client * 4);
        if (i >= MAXEX) continue;
        const uint32_t slot = count_up(bars + 64 + 56 * 4);
        const uint32_t id = eh < 32 ? eh * 8 + ew - 32 : ew < 32 ? ew * 8 + eh - 32 : (eh & 7) * 64 + ((ew - 32) & 63);
        st_pair(scr->mail[client] + i, id | (request(scr, slot < EARLY ? slot : QUEUE, pos, eh, ew, tap) << 16), epoch);
      }
      __syncthreads();
      if (tid < GRID) st_pair(scr->mail[tid] + MAXEX, lds32(bars + 64 + tid * 4), epoch);
      if (tid == 0) {
        scr->ready[3] = epoch;
        scr->ready[8 + ((epoch >> 7) & 1 ^ 1)] = 0;
      }
      TSE(2);
    } else if (wid < 12) {
      const int half = wid >= 6, q = tid - half * 192;
      const uint32_t lin = (q >> 6) * 64 + ((q >> 2) & 15) * 192 + (q & 3) * 16;
      const int e = kj * 192 + (q ^ ((q >> 3) & 3));
      uint32_t ta0 = 0, tb0 = 0, tc0 = 0;
#pragma unroll 1
      for (int c = half; c < 4; c += 2) {
        uint4 g[3], u[4];
        const uint32_t ta = clock32();
        mbar_wait(bars + c * 8);
        const uint32_t tb = clock32();
#pragma unroll
        for (int k = 0; k < 3; k++) lds128(&g[k].x, sbase + (18 + c) * SLOT + k * 3072 + lin);
#pragma unroll
        for (int i = 0; i < 4; i++) {
          float o[4][2];
#pragma unroll
          for (int e = 0; e < 2; e++) {
            const float a = e ? bf16hi((&g[0].x)[i]) : bf16lo((&g[0].x)[i]), bb = e ? bf16hi((&g[1].x)[i]) : bf16lo((&g[1].x)[i]);
            const float cc = e ? bf16hi((&g[2].x)[i]) : bf16lo((&g[2].x)[i]);
            const float s = fmaf(0.25f, cc, a), t = fmaf(0.25f, a, cc);
            o[0][e] = fmaf(0.5f, bb, s);
            o[1][e] = fmaf(-0.5f, bb, s);
            o[2][e] = fmaf(0.5f, bb, t);
            o[3][e] = fmaf(-0.5f, bb, t);
          }
#pragma unroll
          for (int k = 0; k < 4; k++) (&u[k].x)[i] = pack2(o[k][0], o[k][1]);
        }
        if (c >= 2) asm volatile("bar.sync 2, 416;\n" ::: "memory");
#pragma unroll
        for (int k = 0; k < 4; k++) scr->u[(c * 4 + k) * 576 + e] = u[k];
        asm volatile("bar.arrive 1, 416;\n" ::: "memory");
      }
      if (!half) {
        mbar_wait(bars + 4 * 8);
#pragma unroll 6
        for (int c = 0; c < 12; c++) {
          uint4 v;
          lds128(&v.x, sbase + (c % 6 >> 1) * 6 * SLOT + (c / 6 * 6 + kj) * 6144 + (c & 1) * 3072 + lin);
          scr->w[c * 576 + e] = v;
        }
      }
      asm volatile("bar.arrive 3, %0;\n" ::"r"(512 + (epoch & never)) : "memory");
    } else if (wid == 12) {
#pragma unroll 1
      for (int r = 0; r < 3; r++) {
        asm volatile("bar.sync %0, %1;\n" ::"r"(r < 2 ? 1 : 3), "r"((r < 2 ? 416 : 512) + (epoch & never)) : "memory");
        if (elect_one()) {
          asm volatile("red.release.gpu.global.add.u32 [%0], %1;\n" ::"l"(scr->ready + r), "r"(kj ? 32 : 64) : "memory");
          if (r == WAT) load_w();
          TSE(8 + r);
        }
        __syncwarp();
        if (r == 0) asm volatile("bar.arrive 2, 416;\n" ::: "memory");
      }
    } else {
      asm volatile("bar.arrive 3, %0;\n" ::"r"(512 + (epoch & never)) : "memory");
    }
    const uint32_t dl = sbase + 18 * SLOT + 4 * 12288 + wid * 384;
#pragma unroll 1
    for (int slot = (wid == 12 ? 15 : wid > 12 ? 15 - wid : 14 - wid) * 4 + (kj ^ 3); slot < QUEUE; slot += 64) {
      uint2 rq;
#pragma unroll 1
      for (uint32_t spin = 0;; spin++) {
        uint32_t done[2];
        ld_pair(&rq.x, scr->req + slot);
        if (slot < EARLY) {
          ld_pair(done, scr->mail[56] + MAXEX);
          if (rq.y || (done[1] == epoch && slot >= done[0])) break;
        } else {
          asm volatile("ld.acquire.gpu.global.u32 %0, [%1];\n" : "=r"(done[1]) : "l"(scr->ready + 6) : "memory");
          if (rq.y) break;
          if (done[1] == epoch) {
            asm volatile("ld.relaxed.gpu.global.u32 %0, [%1];\n" : "=r"(done[0]) : "l"(scr->ready + 8 + ((epoch >> 7) & 1)) : "memory");
            if (slot - EARLY >= done[0]) break;
          }
        }
        if (spin > (1u << 22)) __trap();
        __nanosleep(100);
      }
      if (!rq.y) continue;
      __syncwarp();
      TSE(4);
      if (lane == 0) scr->req[slot] = make_uint2(0, 0);
      const int tap = rq.y & 15, ki = (tap * 11) >> 5, gy = (int)bf16lo(rq.x), gx = (int)bf16hi(rq.x);
      const int cy = min(max((int)((rq.y >> 12) & 255) + ki - 1, 0), IH - 1), cx = min(max((int)((rq.y >> 4) & 255) + tap - ki * 3 - 1, 0), IW - 1);
      if (lane < 24) {
        const uint2* pc = reinterpret_cast<const uint2*>(x) + lane;
        const int p = (gy * IW + gx) * 24, sx = gx < IW - 1 ? 24 : 0, sy = gy < IH - 1 ? IW * 24 : 0;
        const uint2 v0 = __ldg(pc + p), v1 = __ldg(pc + p + sx), v2 = __ldg(pc + p + sy), v3 = __ldg(pc + p + sy + sx);
        const uint2 c = __ldg(pc + (cy * IW + cx) * 24);
        uint32_t q0, q1;
        coefs(frac2(rq.x), q0, q1);
        const uint32_t d0 = hsub2(blend(q0, q1, v0.x, v1.x, v2.x, v3.x), c.x), d1 = hsub2(blend(q0, q1, v0.y, v1.y, v2.y, v3.y), c.y);
        const uint32_t dd[4] = {__byte_perm(d0, 0, 0x1010), __byte_perm(d0, 0, 0x3232), __byte_perm(d1, 0, 0x1010), __byte_perm(d1, 0, 0x3232)};
        sts128(dl + lane * 16, dd);
      }
      __syncwarp();
      TSE(5);
      mbar_wait(bars + 4 * 8);
      TSE(6);
      float sum[8] = {};
      const int l24 = min(lane, 23);
#pragma unroll 1
      for (int b = 0; b < 6; b++) {
        uint32_t part[4] = {};
#pragma unroll
        for (int i = 0; i < 8; i++) {
          uint32_t wv[4];
          lds128(wv, sbase + (b >> 1) * 6 * SLOT + tap * 6144 + (b & 1) * 3072 + i * 384 + l24 * 16);
          const uint32_t d = lds32(dl + (b * 16 + i * 2 + (l24 >= 12)) * 4);
#pragma unroll
          for (int k = 0; k < 4; k++) part[k] = hfma2(d, wv[k], part[k]);
        }
#pragma unroll
        for (int k = 0; k < 4; k++) {
          sum[k * 2] += bf16lo(part[k]);
          sum[k * 2 + 1] += bf16hi(part[k]);
        }
      }
#pragma unroll
      for (int k = 0; k < 8; k++) sum[k] += __shfl_down_sync(0xffffffffu, sum[k], 12);
      if (lane < 12) {
#pragma unroll
        for (int k = 0; k < 4; k++)
          asm volatile("st.relaxed.gpu.global.v2.u32 [%0], {%1, %2};\n" ::"l"(scr->res[slot] + lane * 4 + k), "r"(pack2(sum[k * 2], sum[k * 2 + 1])), "r"(epoch) : "memory");
      }
      TSE(1);
    }
    mbar_wait(bars + 4 * 8);
  } else if (wid < 8) {
    const int wg = wid >> 2, warp = wid & 3;
    if (cta < 48) {
    uint32_t cf[36];
#pragma unroll
    for (int i = 0; i < 9; i++) cf[i] = o9[i];
    asm volatile("bar.sync 0, 512;\n" ::: "memory");
    {
      const uint32_t base = pack2((float)f, (float)g), sel = band ? 0x1032u : 0x3210u;
      const uint32_t tab = sbase + SM_YT + wid * 1152;
      uint32_t bad = 0;
#pragma unroll
      for (int a = 0; a < 3; a++)
#pragma unroll
        for (int b = 0; b < 3; b++) {
          const uint32_t gp = hadd2(base, tap_delta(a, b));
          const uint32_t pos = hmin2(hmax2(hadd2(gp, __byte_perm(cf[a * 3 + b], 0, sel)), 0u), 0x435f435fu);
          uint32_t d = hsub2(pos, hmin2(gp, 0x435f435fu));
          if ((d & 0x7fff7fffu) > 0x3f80u) {
            bad = 1;
            d = a == 0 && f == 0 ? 0x3f80u : 0u;
          }
          sts32(tab + (lane & 7) * 144 + (b * 12 + (lane >> 3) * 3 + a) * 4, YPRMT ? (d << 16) | (d & 0x8000u ? 0x3210u : 0x7654u) : hmin2(hmax2(__byte_perm(d, 0, 0x1010), 0x0000ff80u), 0x7f800000u));
        }
      if (bad && g >= 34) sts32(bars + O_CNT, FAILED);
      __syncwarp();
      arrive_if(lane == 0 ? bars + B_OS * 8 : 0u);
      asm volatile("setmaxnreg.inc.sync.aligned.u32 224;\n");
      __syncwarp();
#pragma unroll
      for (int i = 0; i < 9; i++) lds128(cf + i * 4, tab + (lane >> 2) * 144 + i * 16);
    }
    uint32_t xa[3];
#pragma unroll
    for (int b = 0; b < 3; b++)
      xa[b] = swz(sbase + SM_YX + ((wid * 4 + (lane >> 4)) * 10 + min((lane & 7) + b, IW - g0)) * 64, (lane >> 3) & 1);
    float acc[2][48];
    uint32_t X[2][16], A[2][12];
    auto fetch = [&](uint32_t* r, uint32_t a) {
#pragma unroll
      for (int i = 0; i < 4; i++) ldsm4(r + i * 4, (a ^ ((i & 1) * 32)) + i * 1280);
    };
    uint64_t bd = w_desc(sbase);
    uint32_t wf = bars + B_WF * 8;
    mbar_wait(bars + B_XF * 8);
    if (YLAG && wg) { const uint32_t t1 = clock32(); wait_until(t1, YLAG); }
    TSE(0);
    fetch(X[0], xa[0]);
    mbar_wait(wf);
#pragma unroll 1
    for (int s = 0; s < 3; s++) {
#pragma unroll
      for (int n = 0; n < 6; n++) {
        const int b = n >> 1;
        if (n == 5) {
          mbar_wait(bars + (B_XF + min(s + 1, 2)) * 8);
#pragma unroll
          for (int k = 0; k < 3; k++) xa[k] += s < 2 ? YSLICE : 0;
        }
        fetch(X[~n & 1], xa[(n + 1) % 6 >> 1] ^ ((~n & 1) * 32));
        const uint32_t* xr = X[n & 1];
        uint32_t D[7][2];
#pragma unroll
        for (int j = 0; j < 7; j++)
#pragma unroll
          for (int e = 0; e < 2; e++) D[j][e] = hsub2(xr[(j + 1) * 2 + e], xr[j * 2 + e]);
#pragma unroll
        for (int t = 0; t < 2; t++) {
          wgmma_wait<1>();
#pragma unroll
          for (int a = 0; a < 3; a++)
#pragma unroll
            for (int i = 0; i < 4; i++) {
              const int o = t * 2 + (i & 1), e = i >> 1, j = o + a + 1;
              const uint32_t c = cf[b * 12 + o * 3 + a];
              A[t][a * 4 + i] = YPRMT ? hfma2_hi(c, prmt(D[j - 1][e], D[j][e], c), xr[j * 2 + e]) : hfma2_hi(c, D[j][e], hfma2_lo(c, D[j - 1][e], xr[j * 2 + e]));
            }
          wgmma_fence();
#pragma unroll
          for (int a = 0; a < 3; a++) wgmma_rs(acc[t], A[t] + a * 4, bd + n * (SLOT >> 4) + a * 192, (n | a) ? 1 : s);
          wgmma_commit();
        }
        if (n & 1) mbar_wait(wf + (b + 1) * 8);
        if (n & 1) TSB(10 + s * 3 + b);
        if (n == 1 && s == 1 && elect_one()) arrive_if(bars + B_WE * 8);
      }
      bd += 6 * SLOT >> 4;
      wf += 24;
    }
    TSE(1);
    const int lane = thread_id() & 31;
    const uint32_t stg = sbase + wg * 3 * SLOT + (wid & 3) * 2048 + (lane & 15) * 64 + ((((lane >> 4) ^ (lane >> 1)) & 3) << 4);
    wgmma_wait<1>();
    acc_fence(acc[0]);
#pragma unroll
    for (int jp = 0; jp < 6; jp++) stage16<8192>(acc[0], jp, stg);
    wgmma_wait<0>();
    acc_fence(acc[1]);
#pragma unroll
    for (int jp = 0; jp < 6; jp++) stage16<8192>(acc[1], jp, stg + 1024);
    proxy_fence();
    __syncwarp();
    arrive_if(lane == 0 ? bars + (B_ST + wg * 4) * 8 : 0u);
    } else if (cta < NI) {
      asm volatile("bar.sync 0, 512;\n" ::: "memory");
      asm volatile("setmaxnreg.inc.sync.aligned.u32 224;\n");
    } else {
    const int tid = thread_id(), lane = tid & 31;
    {
      uint32_t g[3][3][4], src[3], dst[3];
#pragma unroll
      for (int r = 0; r < 3; r++) {
        const int q = r < 2 ? tid + r * 256 : 512 + (tid & 63), b = q >> 6, kj = (b * 11) >> 5;
        src[r] = sbase + SM_RAW + kj * (6144 - 192) + b * 64 + ((q >> 2) & 15) * 192 + (q & 3) * 16;
        dst[r] = sbase + SM_W + (q ^ ((q >> 3) & 3)) * 16;
      }
      asm volatile("bar.sync 0, 512;\n" ::: "memory");
      mbar_wait(bars + (B_WF + 1) * 8);
#pragma unroll 1
      for (int c = 0; c < 2; c++) {
        const bool extra = (wid >> 1) == 2 + c;
#pragma unroll
        for (int r = 0; r < 3; r++)
#pragma unroll
          for (int k = 0; k < 3; k++)
            if (r < 2 || extra) lds128(g[r][k], src[r] + c * 3072 + k * 2 * SLOT);
#pragma unroll
        for (int r = 0; r < 3; r++)
          if (r < 2 || extra) u_math16(g[r], dst[r] + c * 4 * SLOT);
        proxy_fence();
        __syncwarp();
        arrive_if(lane == 0 ? bars + (B_WF + c * 4) * 8 : 0u);
      }
    }
    asm volatile("setmaxnreg.inc.sync.aligned.u32 224;\n");
    float m[4][48];
    const uint32_t vb = sbase + SM_V + wg * UNIT;
    const uint64_t bd0 = w_desc(sbase + SM_W), ad12 = a_desc(vb + 2 * PLANE), ad05 = a_desc(vb + (wg ? 4 * PLANE : 0));

    const uint64_t d34 = wg ? -(2 * PLANE >> 4) : 2 * PLANE >> 4;
    uint64_t ad = ad12;
    uint32_t wf = bars + B_WF * 8;
#pragma unroll 1
    for (int sl = 0; sl < 3; sl++) {
      {
        uint32_t a[4], d[6][2];
#pragma unroll
        for (int j = 0; j < 4; j++) a[j] = swz(vb + j * PLANE + ((tid & 127) >> 3) * 64, lane >> 1) + (lane & 1) * 8;
        const uint32_t a5 = y0 == 216 && ((wg ^ ry) & 1) ? a[0] : a[1], o34 = wg ? 0 : 4 * PLANE;
        mbar_wait(bars + (B_XF + sl * 2 + wg) * 8);
#pragma unroll
        for (int i = 4 - VC; i < 4; i++) {
          v_load(d, a, a5, sl * 2 * UNIT + i * 1024);
          v_store(d, a, 4 * PLANE - o34, o34, sl * 2 * UNIT + i * 1024);
        }
        proxy_fence();
        __syncwarp();
        arrive_if(lane == 0 ? bars + (B_XR + sl * 2 + wg) * 8 : 0u);
        TSB(8 + sl * 3);
        mbar_wait(wf);
        mbar_wait(bars + (B_XR + sl * 2 + wg) * 8);
        TSB(9 + sl * 3);
      }
#pragma unroll
      for (int n = 0; n < 8; n++) {
        const int k = n & 3;
        wgmma_fence();
#pragma unroll
        for (int kj = 0; kj < 3; kj++)
          wgmma_ss(m[k], (k < 2 ? ad : ad + d34) + (k & 1) * (PLANE >> 4) + n / 4 * 2 + kj * 4, bd0 + n * (SLOT >> 4) + kj * 192, (n / 4 | kj) ? 1 : sl);
        wgmma_commit();
        if (n < 7) {
          if (sl || n == 3) mbar_wait(wf + (n + 1) * 8);
          wgmma_wait<1>();
          if (warp == 0 && n) asm volatile("bar.arrive %0, 96;\n" ::"r"(7 + n) : "memory");
        }
      }
      if (!LATE4 && sl == 2 && wg) asm volatile("bar.arrive 4, 256;\n" ::: "memory");
      wgmma_wait<1>();
      if (LATE4 && sl == 2 && wg) asm volatile("bar.arrive 4, 256;\n" ::: "memory");
      if (warp == 0) asm volatile("bar.arrive 14, 96;\n" ::: "memory");
      wgmma_wait<0>();
      if (warp == 0) asm volatile("bar.arrive 15, 96;\n" ::: "memory");
      TSB(10 + sl * 3);
      ad += 2 * UNIT >> 4;
      wf += 64;

    }
    const uint32_t stg = sbase + SM_X + 2 * UNIT + wg * 21504 + warp * 1024 + (lane & 15) * 64 + ((((lane >> 4) ^ (lane >> 1)) & 3) << 4);
    const uint32_t stb = lane == 0 ? bars + (B_ST + wg * 4) * 8 : 0u;
    auto publish = [&](int k) {
      proxy_fence();
      __syncwarp();
      arrive_if(stb ? stb + k * 8 : 0u);
    };
#pragma unroll
    for (int k = 0; k < 4; k++) acc_fence(m[k]);
    float dep = 0.f;
#pragma unroll
    for (int i0 = 0; i0 < 48; i0 += TGRP) {
#pragma unroll
      for (int e = 0; e < TX; e++) asm volatile("add.f32 %0, %0, %0;\n" : "+f"(dep));
      const float k0 = __uint_as_float((__float_as_uint(dep) & never) | 0xbf088889u);
      const float k1 = __uint_as_float((__float_as_uint(dep) & never) | 0xbf800000u);
#pragma unroll
      for (int i = i0; i < i0 + TGRP; i++) {
        m[0][i] *= k0;
        m[3][i] = fmaf(k1, m[3][i], m[2][i]);
        m[1][i] = fmaf(-8.0f / 15.0f, m[1][i], m[0][i]);
        m[2][i] = fmaf(-0.5f, m[3][i], m[2][i]);
        m[0][i] = fmaf(-0.5f, m[1][i], m[0][i]);
        m[1][i] = fmaf(4.0f / 15.0f, m[2][i], m[1][i]);
        m[0][i] = fmaf(4.0f / 15.0f, m[3][i], m[0][i]);
        m[2][i] = fmaf(0.25f, m[1][i], m[2][i]);
        m[3][i] = fmaf(0.25f, m[0][i], m[3][i]);
        dep = m[TDEP][i];
        if ((i & 7) == 7) {
          stage16<4096>(m[2], i >> 3, stg);
          stage16<4096>(m[0], i >> 3, stg + 2 * UNIT);
        }
      }
    }
    publish(0);
    TSB(20);
    asm volatile("bar.sync %0, 256;\n" ::"r"(4 + wg) : "memory");
    TSB(21);
    const uint64_t bdx = w_desc(sbase + SM_X);
    const uint32_t s05 = vb + (wg ? 4 * PLANE : 0) + warp * 1024 + (lane & 15) * 64;
#pragma unroll
    for (int j = 0; j < 12; j++) {
      float* acc = j < 6 ? m[1] : m[3];
      const int c = j % 6;
      const uint64_t ad = ad05 + (c >> 1) * (2 * UNIT >> 4) + (c & 1) * 2 + (j < 6 ? 0 : PLANE >> 4);
      const uint64_t bd = j < 3 ? bdx + j * (SLOT >> 4) : j == 3 ? bdx + ((2 * UNIT + 12288) >> 4) : bd0 + (j - 4) * (SLOT >> 4);
      if (j != 1 && j != 2) mbar_wait(bars + (B_WF + 24 + j) * 8);
      wgmma_fence();
#pragma unroll
      for (int kj = 0; kj < 3; kj++) wgmma_ss(acc, ad + kj * 4, bd + kj * 192);
      wgmma_commit();
      if (j == 3 || j == 5 || j == 7 || j == 9 || j == 11) TSB(22 + j);
      if (PW >= 0 && j < 11) wgmma_wait<PW < 0 ? 0 : PW>();
      if (j == HAND && !wg) asm volatile("bar.arrive 5, 256;\n" ::: "memory");
      if (Y0M == 0) {
        if (j == 7) {
          wgmma_wait<2>();
          acc_fence(m[1]);
        }
        if (j >= 7 && j <= 9) {
#pragma unroll
          for (int jp = j * 2 - 14; jp < j * 2 - 12; jp++) stage16<2 * UNIT>(m[1], jp, swz(s05, lane >> 4));
        }
      } else if (j == 5 + Y0M) {
        wgmma_wait<Y0M>();
        acc_fence(m[1]);
#pragma unroll
        for (int jp = 0; jp < 6; jp++) stage16<2 * UNIT>(m[1], jp, swz(s05, lane >> 4));
      }
      if (j == PUB1) publish(1);
    }
    wgmma_wait<0>();
    acc_fence(m[3]);
    const uint32_t tend = clock32();
    if (HAND == 13 && !wg) asm volatile("bar.arrive 5, 256;\n" ::: "memory");
#pragma unroll
    for (int jp = 0; jp < 6; jp++) stage16<2 * UNIT>(m[3], jp, swz(s05 + PLANE, lane >> 4));
    if (HAND == 12 && !wg) asm volatile("bar.arrive 5, 256;\n" ::: "memory");
    publish(2);
    }
    int rounds = 1;
    const int tid = thread_id(), lane = tid & 31;
    if (cta < 48 || cta >= NI) {
      mbar_wait(bars + B_OK * 8);
      rounds = lds32(bars + O_VER) != FAILED ? 0 : cta < 48 ? 2 : 4;
      rounds = __shfl_sync(0xffffffffu, rounds, 0);
    }
    if (rounds) {
      const bool lead = warp == 0 && elect_one();
      if (rounds > 1) {
        if (tid == 0) {
#pragma unroll
          for (int i = 0; i < 15; i++) mbar_init(bars + (B_G + i) * 8, 1);
          asm volatile("fence.mbarrier_init.release.cluster;\n" ::: "memory");
        }
        proxy_fence();
        asm volatile("bar.sync 3, 256;\n" ::: "memory");
      }
      const uint32_t win = sbase + SM_GX + wg * 3 * GSLICE, gxb = bars + (B_G + 9 + wg * 3) * 8;
      const uint64_t bd0 = w_desc(sbase);
      float acc[48];
#pragma unroll 1
      for (int r = 0; r < rounds; r++) {
        int ty, tx;
        if (cta >= NI) { ty = y0; tx = x0 + r * 16 + wg * 8; }
        else if (cta < 48) { ty = band ? g0 : r * 16 + wg * 8; tx = band ? r * 16 + wg * 8 : g0; }
        else { ty = (cta & 1) * 8 + wg * 16; tx = (cta & 2) * 4 + ((cta >> 2 ^ wg) & 1) * 16; }
        if (lead && rounds > 1) {
#pragma unroll 1
          for (int sl = 0; sl < 3; sl++) {
            mbar_expect_tx(gxb + sl * 8, GSLICE);
            tma_load_3d(win + sl * GSLICE, &tm.gx, gxb + sl * 8, sl * 32, tx - 2, ty - 2);
            if (r == 0) {
#pragma unroll 1
              for (int ki = 0; ki < 3; ki++) {
                if (!wg) mbar_expect_tx(bars + (B_G + sl * 3 + ki) * 8, 2 * SLOT);
                tma_load_5d(sbase + ((sl * 3 + ki) * 2 + wg) * SLOT, &tm.bw[1], bars + (B_G + sl * 3 + ki) * 8, sl * 32 + wg * 16, 0, ki);
              }
            }
          }
        }
        const int ph = ty + warp * 2 + ((lane >> 3) & 1), pw = tx + (lane & 7);
        const uint32_t* op = offs + (ph * IW + pw) * 9;
        const uint32_t base = pack2((float)ph, (float)pw);
        uint32_t ent[9], cf[36], need = 0, out = 0;
#pragma unroll
        for (int m = 0; m < 9; m++) ent[m] = __ldg(op + m);
#pragma unroll
        for (int m = 0; m < 9; m++) {
          const uint32_t pos = clip2(hadd2(hadd2(base, tap_delta(m / 3, m % 3)), ent[m])), fr = frac2(pos);
          const uint32_t iy = (int)bf16lo(pos) - (ty - 2), ix = (int)bf16hi(pos) - (tx - 2);
          out |= max(iy, ix) > 10;
          need |= ((fr >> 16 ? 1u : 0u) | (fr & 0xffffu ? 2u : 0u) | (fr >> 16 && (fr & 0xffffu) ? 4u : 0u)) << (m * 3);
          const uint32_t pp = (iy * 12 + ix) * 0x10001u + 0x10000u;
          ent[m] = (pp * 64 + ((pp << 3) & 0x300030u)) ^ ((lane >> 4) * 0x100010u);
          coefs(__shfl_sync(0xffffffffu, fr, lane >> 2), cf[m * 4], cf[m * 4 + 1]);
          coefs(__shfl_sync(0xffffffffu, fr, (lane >> 2) + 8), cf[m * 4 + 2], cf[m * 4 + 3]);
        }
        need = __reduce_or_sync(0xffffffffu, need);
        asm volatile("{\n.reg .pred p;\nsetp.ne.u32 p, %0, 0;\nbarrier.red.popc.u32 %0, %1, 128, p;\n}\n" : "+r"(out) : "r"(1 + wg) : "memory");
        out = __shfl_sync(0xffffffffu, out, 0);
        TSE(0);
        if (!out) {
          uint32_t C[2][4][8], A[2][8];
#pragma unroll
          for (int i = 0; i < 64; i++) C[0][0][i] = 0;
          auto fetch = [&](uint32_t (*c)[8], int m, uint32_t slice) {
            const uint32_t a0 = (ent[m] & 0xffffu) + slice, a1 = (ent[m] >> 16) + slice;
#pragma unroll
            for (int h = 0; h < 2; h++) {
              ldsm4(c[0] + h * 4, a0 ^ (h * 32));
              ldsm4_if(c[1] + h * 4, a1 ^ (h * 32), need & (1 << (m * 3)));
              ldsm4_if(c[2] + h * 4, (a0 ^ (h * 32) ^ 32) + 768, need & (2 << (m * 3)));
              ldsm4_if(c[3] + h * 4, (a1 ^ (h * 32) ^ 32) + 768, need & (4 << (m * 3)));
            }
          };
#pragma unroll 1
          for (int sl = 0; sl < 3; sl++) {
            const uint32_t slice = win + sl * GSLICE;
            const uint64_t bd = bd0 + sl * (6 * SLOT >> 4);
            mbar_wait(gxb + sl * 8, r & 1);
            fetch(C[0], 0, slice);
#pragma unroll
            for (int m = 0; m < 9; m++) {
              if (m < 8) fetch(C[~m & 1], m + 1, slice);
              if (m % 3 == 0) mbar_wait(bars + (B_G + sl * 3 + m / 3) * 8);
              if (m >= 2) wgmma_wait<1>();
#pragma unroll
              for (int i = 0; i < 8; i++)
                A[m & 1][i] = blend(cf[m * 4 + (i & 1) * 2], cf[m * 4 + (i & 1) * 2 + 1], C[m & 1][0][i], C[m & 1][1][i], C[m & 1][2][i], C[m & 1][3][i]);
              wgmma_fence();
              wgmma_rs(acc, A[m & 1], bd + m / 3 * (2 * SLOT >> 4) + m % 3 * 192, m ? 1 : sl);
              wgmma_rs(acc, A[m & 1] + 4, bd + (m / 3 * 2 + 1) * (SLOT >> 4) + m % 3 * 192);
              wgmma_commit();
            }
            wgmma_wait<0>();
          }
        } else {
#pragma unroll 1
          for (int i = 0; i < 12; i++) mbar_wait(i < 9 ? bars + (B_G + i) * 8 : gxb + (i - 9) * 8, i < 9 ? 0 : r & 1);
          const uint32_t scratch = win + warp * 3072 + lane * 16;
#pragma unroll 1
          for (int m = 0; m < 9; m++) {
            const int ki = (m * 11) >> 5;
            const uint32_t pos = clip2(hadd2(pack2((float)(ph + ki - 1), (float)(pw + m - ki * 3 - 1)), __ldg(op + m)));
            const int gy = (int)bf16lo(pos), gx = (int)bf16hi(pos), sx = gx < IW - 1 ? 12 : 0, sy = gy < IH - 1 ? IW * 12 : 0;
            const uint4* pc = x + (gy * IW + gx) * 12 + (lane >> 4);
            uint32_t q0, q1, V[6][4][4], A[6][4];
            coefs(frac2(pos), q0, q1);
#pragma unroll
            for (int k = 0; k < 6; k++)
#pragma unroll
              for (int c = 0; c < 4; c++) ldg128(V[k][c], pc + k * 2 + (c & 1) * sx + (c >> 1) * sy);
#pragma unroll
            for (int k = 0; k < 6; k++) {
#pragma unroll
              for (int i = 0; i < 4; i++) V[k][0][i] = blend(q0, q1, V[k][0][i], V[k][1][i], V[k][2][i], V[k][3][i]);
              sts128(scratch + k * 512, V[k][0]);
            }
            __syncwarp();
#pragma unroll
            for (int k = 0; k < 6; k++) ldsm4(A[k], scratch + k * 512);
            wgmma_fence();
#pragma unroll
            for (int k = 0; k < 6; k++) wgmma_rs(acc, A[k], bd0 + ((k >> 1) * 6 + ki * 2 + (k & 1)) * (SLOT >> 4) + (m - ki * 3) * 192, k ? 1 : m);
            wgmma_commit();
            wgmma_wait<0>();
          }
        }
        acc_fence(acc);
        TSE(1);
        asm volatile("bar.sync %0, 128;\n" ::"r"(1 + wg) : "memory");
#pragma unroll
        for (int jp = 0; jp < 6; jp++) stage16<4096>(acc, jp, win + warp * 1024 + (lane & 15) * 64 + ((((lane >> 4) ^ (lane >> 1)) & 3) << 4));
        proxy_fence();
        asm volatile("bar.sync %0, 128;\n" ::"r"(1 + wg) : "memory");
        if (lead) {
          tma_store(&tm.gout, win, tx, ty);
          asm volatile("cp.async.bulk.commit_group;\ncp.async.bulk.wait_group.read 0;\n" ::: "memory");
          TSE(2);
        }
      }
    }
  } else if (wid < 12) {
    asm volatile("setmaxnreg.dec.sync.aligned.u32 %0;\n" ::"n"(R2));
    const int tid = thread_id(), lane = tid & 31;

    const bool one = elect_one();
    if (one && cta < NI) {
#pragma unroll
      for (int i = 0; i < 4; i++) mbar_init(bars + (B_G + (wid - 8) * 4 + i) * 8, 1);
      asm volatile("fence.mbarrier_init.release.cluster;\n" ::: "memory");
    }
    if (one && cta >= NI) {
#pragma unroll
      for (int i = 0; i < 7; i++) mbar_init(bars + (B_WF + 8 + (wid - 8) * 7 + i) * 8, 1);
      if (wid < 10) mbar_init(bars + (B_WF + (wid - 8) * 4) * 8, 8);
      mbar_init(bars + (B_UR + wid - 8) * 8, 1);
      asm volatile("fence.mbarrier_init.release.cluster;\n" ::: "memory");
    }
    asm volatile("bar.arrive 3, 256;\n" ::: "memory");
    asm volatile("bar.sync 0, 512;\n" ::: "memory");
    if (cta >= NI) {
      uint32_t a[4], d[2][6][2];
#pragma unroll
      for (int j = 0; j < 4; j++) a[j] = swz(sbase + SM_V + j * PLANE + ((tid & 127) >> 3) * 64, lane >> 1) + (lane & 1) * 8;
      const bool bot = y0 == 216;
      uint32_t tsv = 0;
      uint32_t off = 0;
#pragma unroll 1
      for (int u = 0; u < 6; u++) {
        const uint32_t a5 = bot && ((u ^ ry) & 1) ? a[0] : a[1], o34 = u & 1 ? 0 : 4 * PLANE;
        mbar_wait(bars + (B_XF + u) * 8);
        if (VGATE && u >= 1) mbar_wait(bars + (B_XR + u - 1) * 8);
        if (R2 == 40) v_load(d[0], a, a5, off);
#pragma unroll
        for (int i = 0; i < 4 - VC; i++) {
          if (R2 == 40) {
            if (i < 3 - VC) v_load(d[~i & 1], a, a5, off + (i + 1) * 1024);
            v_store(d[i & 1], a, 4 * PLANE - o34, o34, off + i * 1024);
          } else {
            v_load(d[0], a, a5, off + i * 1024);
            v_store(d[0], a, 4 * PLANE - o34, o34, off + i * 1024);
          }
        }
        if ((u & 3) == (wid & 3) && lane < 16) {
          const uint32_t h = off + 4096 - (wid & 2) * 256;
          v_load(d[1], a, a5, x0 == 160 && lane >= 8 ? h - 64 : h);
          v_store(d[1], a, 4 * PLANE - o34, o34, h);
        }
        proxy_fence();
        __syncwarp();
        arrive_if(one ? bars + (B_XR + u) * 8 : 0u);
        if (TSBON && lane == u) tsv = clock32() - tstart;
        off += UNIT + ((u ^ wid) & 1 ? -256 : 256);
      }
    }
  } else {
    asm volatile("setmaxnreg.dec.sync.aligned.u32 %0;\n" ::"n"(64 - R2));
    const int tid = thread_id(), lane = tid & 31;
    const bool one = elect_one();
    if (wid != 12) {
      if (one) {
        if (cta >= NI) {
          if (wid == 13) {
#pragma unroll
            for (int i = 0; i < 6; i++) mbar_init(bars + (B_XR + i) * 8, 8);
          } else if (wid == 15) {
#pragma unroll
            for (int i = 1; i < 6; i++) mbar_init(bars + (B_XF + i) * 8, 1);
          }
        } else {
#pragma unroll
          for (int i = 0; i < 3; i++) mbar_init(bars + (B_WF + 1 + (wid - 13) * 3 + i) * 8, 1);
          mbar_init(bars + (wid == 13 ? B_WE : B_UR + wid - 14) * 8, wid == 13 ? 8 : 1);
          if (wid < 15) mbar_init(bars + (B_XF + wid - 12) * 8, 1);
        }
        if (wid == 14) {
#pragma unroll
          for (int i = 0; i < 8; i++) mbar_init(bars + (B_ST + i) * 8, 4);
#pragma unroll
          for (int i = B_OF; i <= B_OK; i++) mbar_init(bars + i * 8, i != B_OS ? 1 : cta < NI ? 8 : 2);
          sts64(bars + O_CNT, 0, 0);
          sts64(bars + O_CNT + 8, 0, 0);
        }
        asm volatile("fence.mbarrier_init.release.cluster;\n" ::: "memory");
      }
      asm volatile("bar.arrive 3, 256;\n" ::: "memory");
      asm volatile("bar.sync 0, 512;\n" ::: "memory");
      if (cta >= 48 && cta < NI) {
        if (wid == 15 && one) asm volatile("red.relaxed.gpu.global.add.u32 [%0], 1;\n" ::"l"(scr->ready + 6) : "memory");
      } else {
        uint32_t epoch = 0;
        if (cta >= NI && wid < 15) {
          const uint32_t lim = (pack2((float)max(y0, 34) - 1.5f, (float)max(x0, 34) - 1.5f) & 0x7f807f80u) - 0x04000400u;
          uint32_t big = 0;
          mbar_wait(bars + B_OF * 8);
          TSE(6);
#pragma unroll 1
          for (int i0 = 0; i0 < 18; i0 += SCANB) {
            uint32_t v[SCANB][4];
#pragma unroll
            for (int i = 0; i < SCANB; i++) lds128(v[i], sbase + SM_OFF + (tid - 416) * 16 + (i0 + i) * 1024);
#pragma unroll
            for (int i = 0; i < SCANB; i++) {
              const __nv_bfloat162 mx = __hmax2_nan(__hmax2_nan(__habs2(as_bf2(v[i][0])), __habs2(as_bf2(v[i][1]))),
                                                    __hmax2_nan(__habs2(as_bf2(v[i][2])), __habs2(as_bf2(v[i][3]))));
              big = big * 2 + !__hblt2(mx, as_bf2(lim));
            }
          }
          if (big) {
            mbar_wait(bars + B_EP * 8);
            epoch = lds32(bars + O_EPO);
          }
#pragma unroll 1
          for (int k = 0; big; k++) {
            const uint32_t wi = (tid - 416 + (18 - __ffs(big)) * 64) * 4 + (k & 3), id = (wi * 7282) >> 16, tap = wi - id * 9;
            const int ki = (tap * 11) >> 5, h = y0 + (id >> 6), w = x0 + (id & 63);
            const uint32_t gp = pack2((float)(h + ki - 1), (float)(w + (int)tap - ki * 3 - 1)), pos = clip2(hadd2(gp, lds32(sbase + SM_OFF + wi * 4)));
            if (pos != hmin2(gp, 0x435f435fu) && h >= 34 && w >= 34) {
              const uint32_t i = count_up(bars + O_CNT);
              if (i >= MAXEX) break;
              sts32(bars + O_LST + i * 4, id | (request(scr, min(atomicAdd(scr->ready + 8 + ((epoch >> 7) & 1), 1u) + EARLY, QUEUE), pos, h, w, tap) << 16));
            }
            if ((k & 3) == 3) big &= big - 1;
          }
          __syncwarp();
          arrive_if(one ? bars + B_OS * 8 : 0u);
        }
        if (wid == 13) {
          uint32_t m[2] = {}, cnt = 0;
          mbar_wait(bars + B_OS * 8);
          if (cta >= NI) {
            mbar_wait(bars + (B_WF + X5W) * 8);
            if (one) {
              mbar_expect_tx(bars + (B_XF + 5) * 8, UNIT);
              tma_load_3d(sbase + SM_V + 5 * UNIT, &tm.x, bars + (B_XF + 5) * 8, 64, x0 - 1, y0 + (~ry & 1) * 4 - 1);
            }
          }
          TSE(7);
          mbar_wait(bars + B_EP * 8);
          epoch = lds32(bars + O_EPO);
          if (cta >= NI ? x0 == 32 || y0 == 32 : g0 == 32) {
#pragma unroll 1
            for (uint32_t spin = 0;; spin++) {
              ld_pair(m, scr->mail[cta] + min(lane, MAXEX));
              const uint32_t have = __ballot_sync(0xffffffffu, m[1] == epoch);
              cnt = __reduce_max_sync(0xffffffffu, lane == MAXEX ? m[0] : 0u);
              if ((have >> MAXEX) && (cnt > MAXEX || !(~have & ((1u << cnt) - 1)))) break;
              if (spin > (1u << 22)) __trap();
            }
          }
          if (one) asm volatile("red.relaxed.gpu.global.add.u32 [%0], 1;\n" ::"l"(scr->ready + 6) : "memory");
          const uint32_t own = lds32(bars + O_CNT);
          if (own && lane >= cnt) m[0] = lds32(bars + O_LST + ((lane - cnt) & 15) * 4);
          cnt += own;
          if (cnt > MAXEX || __any_sync(0xffffffffu, lane < cnt && m[0] >> 16 == QUEUE)) cnt = FAILED;
          sts32(bars + O_LST + lane * 4, lane < cnt ? m[0] & 511 : 512);
#pragma unroll 1
          for (uint32_t got = 0; got < cnt && cnt != FAILED; got += 4) {
            const uint32_t i = min(got + (lane >> 3), cnt - 1);
            const uint2* r = scr->res[__shfl_sync(0xffffffffu, m[0], i) >> 16] + (lane & 7);
            uint32_t v[12];
#pragma unroll 1
            for (uint32_t spin = 0;; spin++) {
              uint32_t miss = 0;
#pragma unroll
              for (int k = 0; k < 6; k++) ld_pair(v + k * 2, r + k * 8);
#pragma unroll
              for (int k = 0; k < 6; k++) miss |= v[k * 2 + 1] ^ epoch;
              if (__all_sync(0xffffffffu, !miss)) break;
              if (spin > (1u << 22)) __trap();
            }
#pragma unroll
            for (int k = 0; k < 6; k++) sts32(bars + O_COR + i * 192 + (lane & 7) * 4 + k * 32, v[k * 2]);
          }
          if (one) sts32(bars + O_VER, cnt);
          __syncwarp();
          arrive_if(one ? bars + B_OK * 8 : 0u);
          TSE(0);
        } else {
          if (wid == 15) {
            auto poll = [&]() {
              uint32_t v;
              asm volatile("ld.relaxed.gpu.global.u32 %0, [%1];\n" : "=r"(v) : "l"(scr->ready + min(lane, 6)) : "memory");
              return v;
            };
            const uint32_t epoch = (__reduce_max_sync(0xffffffffu, lane == 6 ? poll() : 0u) & ~127u) + 128;
            if (one) sts32(bars + O_EPO, epoch);
            arrive_if(one ? bars + B_EP * 8 : 0u);
            if (cta >= NI) {
              uint32_t v[PFLY], seen = 0;
              wait_until(tstart, POLLT);
#pragma unroll
              for (int i = 0; i < PFLY - 1; i++) {
                v[i] = poll();
                __nanosleep(PGAP);
              }
#pragma unroll 1
              for (uint32_t spin = 0; seen != 7; spin++) {
#pragma unroll
                for (int i = 0; i < PFLY; i++) {
                  v[(i + PFLY - 1) % PFLY] = poll();
                  const uint32_t now = __ballot_sync(0xffffffffu, v[i] == epoch) & ~seen & 7;
                  if (now) {
                    asm volatile("fence.proxy.async.global;\n" ::: "memory");
                    arrive_if((now >> lane) & 1 ? bars + (B_UR + lane) * 8 : 0u);
                    seen |= now;
                    TSB(8 + __popc(seen));
                  }
                }
                if (spin > (1u << 20)) __trap();
              }
            }
            TSE(4);
          }
          const int t = wid & 1;
          mbar_wait(bars + B_OK * 8);
          const uint32_t cnt = lds32(bars + O_VER);
          if (cnt != FAILED) {
            const uint32_t id = lds32(bars + O_LST + lane * 4);
            mbar_wait(bars + (B_ST + t * 4) * 8);
            if (cta < NI) {
              patch(id, t * 128, 128, sbase + t * 3 * SLOT, 8192, bars, lane);
              if (one) tma_store(&tm.bout[band], sbase + t * 3 * SLOT, g0, t * 16);
            } else {
              const int r0 = ((t ^ ry) & 1) * 4;
#pragma unroll 1
              for (int r = 0; r < 4; r++) {
                const uint32_t base = r < 2 ? sbase + SM_X + (2 + r * 2) * UNIT + t * 21504 : sbase + SM_V + t * (UNIT + 4 * PLANE) + (r - 2) * PLANE;
                const uint32_t pitch = r < 2 ? 4096 : 2 * UNIT;
                const int row = r0 + ((2 - r) & 3);
                if (r >= 2) mbar_wait(bars + (B_ST + t * 4 + r - 1) * 8);
                patch(id, row * 64, 64, base, pitch, bars, lane);
#pragma unroll
                for (int k = 0; k < 3; k++)
                  if (one) tma_store3(&tm.out, base + k * pitch, k * 32, x0, y0 + row);
              }
            }
            if (one) asm volatile("cp.async.bulk.commit_group;\ncp.async.bulk.wait_group.read 0;\n" ::: "memory");
            TSE(2);
          }
        }
      }
    } else if (cta < NI) {
        auto load_x = [&](int s) {
          mbar_expect_tx(bars + (B_XF + s) * 8, YSLICE);
          tma_load_3d(sbase + SM_YX + s * YSLICE, &tm.bx[band], bars + (B_XF + s) * 8, s * 32, g0 - 1, -2);
        };
        auto load_w = [&](int p) {
          const int s = (p * 11) >> 5, b = p - s * 3;
          mbar_expect_tx(bars + (B_WF + p) * 8, 2 * SLOT);
#pragma unroll
          for (int h = 0; h < 2; h++)
            tma_load_5d(sbase + (p * 2 + h) * SLOT, &tm.bw[band], bars + (B_WF + p) * 8, s * 32 + h * 16, band ? 0 : b, band ? b : 0);
        };
        asm volatile("bar.sync 3, 256;\n" ::: "memory");
        if (one && cta >= 48) {
#pragma unroll 1
          for (int sl = 0; sl < 3; sl++) {
            wait_until(tstart, sl * GDT);
#pragma unroll
            for (int wg = 0; wg < 2; wg++) {
              mbar_expect_tx(bars + (B_G + 9 + wg * 3 + sl) * 8, GSLICE);
              tma_load_3d(sbase + SM_GX + (wg * 3 + sl) * GSLICE, &tm.gx, bars + (B_G + 9 + wg * 3 + sl) * 8, sl * 32,
                          (cta & 2) * 4 + ((cta >> 2 ^ wg) & 1) * 16 - 2, (cta & 1) * 8 + wg * 16 - 2);
            }
#pragma unroll 1
            for (int i = 0; i < 6; i++) {
              if (!(i & 1)) mbar_expect_tx(bars + (B_G + sl * 3 + (i >> 1)) * 8, 2 * SLOT);
              tma_load_5d(sbase + (sl * 6 + i) * SLOT, &tm.bw[1], bars + (B_G + sl * 3 + (i >> 1)) * 8, sl * 32 + (i & 1) * 16, 0, i >> 1);
            }
          }
        }
        if (one && cta < 48) {
          arrive_if(bars + (B_WF + 9) * 8);
#pragma unroll 1
          for (int p = 1; p < 9; p++) {
            wait_until(tstart, YWT + (p - 1) * YWDT);
            if (p == YP1) load_x(1);
            if (p == YP2) load_x(2);
            if (p == 8) mbar_wait(bars + B_WE * 8);
            load_w(p);
          }
        }
    } else {
        auto load_x = [&](int u) {
          mbar_expect_tx(bars + (B_XF + u) * 8, UNIT);
          tma_load_3d(sbase + SM_V + u * UNIT, &tm.x, bars + (B_XF + u) * 8, (u >> 1) * 32, x0 - 1, y0 + ((u ^ ry) & 1) * 4 - 1);
        };
        asm volatile("bar.sync 3, 256;\n" ::: "memory");
        if (lane < 28) mbar_expect_tx(bars + (B_WF + 8 + lane) * 8, lane == 16 ? 3 * SLOT : lane == 17 || lane == 18 ? 0 : SLOT);
        if (smem_u32(smem) != sbase) __trap();
#pragma unroll 1
        for (int xu = 1; xu <= XN; xu++) {
          wait_until(tstart, XT1 + (xu - 1) * XDT);
          if (xu == 3) mbar_wait(bars + (B_WF + 4) * 8);
          if (one) load_x(xu);
          if (xu == OFFAT && one) {
            mbar_expect_tx(bars + B_OF * 8, 2 * SLOT);
            tma_load_3d(sbase + SM_OFF, &tm.off, bars + B_OF * 8, 0, x0 * 9 / 32, y0);
          }
        }
        const uint4* src = scr->u;
        uint32_t fb = bars + (B_WF + 8) * 8;
#pragma unroll 1
        for (int q = 0; q < 6; q++) {
          mbar_wait(bars + (B_UR + (q >> 1)) * 8);
          if (q == 4) {
            if (one) bulk_load<3 * SLOT>(sbase + SM_X, src, fb);
            if (one) bulk_load<SLOT>(sbase + SM_X + 2 * UNIT + 12288, src + 3 * 576, fb + 24);
            src += 4 * 576;
            fb += 32;
          }
          const uint32_t dst = sbase + SM_W + (q & 1) * 4 * SLOT, id = 8 + (q & 1) * 4;
#pragma unroll
          for (int k = 0; k < 4; k++) {
            asm volatile("bar.sync %0, 96;\n" ::"r"(id + k) : "memory");
            if (one) bulk_load<SLOT>(dst + k * SLOT, src + k * 576, fb + k * 8);
          }
          if (q == 1 && one) {
            if (XN < 4) load_x(4);
          }
          src += 4 * 576;
          fb += 32;
        }
    }
  }
}

typedef CUresult (*EncodeTiledFn)(CUtensorMap*, CUtensorMapDataType, cuuint32_t, void*, const cuuint64_t*,
                                  const cuuint64_t*, const cuuint32_t*, const cuuint32_t*, CUtensorMapInterleave,
                                  CUtensorMapSwizzle, CUtensorMapL2promotion, CUtensorMapFloatOOBfill);

}

extern "C" void kernel_launch(void* const* d_in, const int* in_sizes, int n_in, void* d_out, int out_size) {
  static EncodeTiledFn encode = nullptr;
  static Scratch* scratch = nullptr;
  if (!encode) {
    void* fn = nullptr;
    cudaDriverEntryPointQueryResult qres;
    cudaGetDriverEntryPoint("cuTensorMapEncodeTiled", &fn, cudaEnableDefault, &qres);
    encode = (EncodeTiledFn)fn;
    cudaGetSymbolAddress((void**)&scratch, g_scratch);
    cudaFuncSetAttribute(dcn_kernel, cudaFuncAttributeMaxDynamicSharedMemorySize, SMEM_BYTES);
  }
  uint32_t* tsp = nullptr;
  Maps tm;
  auto make = [&](CUtensorMap* m, void* p, int rank, const cuuint64_t* dims, const cuuint64_t* strides, const cuuint32_t* box, bool swizzle) {
    const cuuint32_t es[5] = {1, 1, 1, 1, 1};
    encode(m, CU_TENSOR_MAP_DATA_TYPE_BFLOAT16, rank, p, dims, strides, box, es, CU_TENSOR_MAP_INTERLEAVE_NONE,
           swizzle ? CU_TENSOR_MAP_SWIZZLE_64B : CU_TENSOR_MAP_SWIZZLE_NONE, CU_TENSOR_MAP_L2_PROMOTION_NONE,
           CU_TENSOR_MAP_FLOAT_OOB_FILL_NONE);
  };
  const cuuint64_t PX = IC * 2, ROW = IW * IC * 2, TAP = IC * IC * 2;
  for (int t = 0; t < 2; t++) {
    const cuuint64_t dims[3] = {IC, IW, IH}, odims[4] = {32, IW, IH, 3}, strides[3] = {t ? ROW : PX, t ? PX : ROW, 64};
    const cuuint32_t xb[3] = {32, 66, 6}, ob[3] = {32, 64, 1}, bxb[3] = {32, 10, 36}, bob[4] = {32, 8, 16, 3};
    if (!t) make(&tm.x, d_in[0], 3, dims, strides, xb, true);
    if (!t) make(&tm.out, d_out, 3, dims, strides, ob, true);
    const cuuint32_t gxb[3] = {32, 12, 12}, gob[4] = {32, 8, 8, 3};
    if (!t) make(&tm.gx, d_in[0], 3, dims, strides, gxb, true);
    if (!t) make(&tm.gout, d_out, 4, odims, strides, gob, true);
    make(&tm.bx[t], d_in[0], 3, dims, strides, bxb, true);
    make(&tm.bout[t], d_out, 4, odims, strides, bob, true);
    const cuuint64_t wdims[5] = {32, IC, 3, 3, 3}, wstrides[4] = {PX, 64, TAP, 3 * TAP};
    const cuuint32_t wb[5] = {32, 16, 3, t ? 3u : 1u, t ? 1u : 3u};
    make(&tm.bw[t], d_in[2], 5, wdims, wstrides, wb, true);
  }
  {
    const cuuint64_t dims[3] = {64, 144, 9}, strides[2] = {128, TAP};
    const cuuint32_t box[3] = {64, 48, 9};
    make(&tm.w, d_in[2], 3, dims, strides, box, false);
    const cuuint64_t cdims[4] = {64, 144, 3, 3}, cstrides[3] = {128, TAP, 3 * TAP};
    const cuuint32_t cbox[4] = {64, 24, 1, 3};
    make(&tm.wc, d_in[2], 4, cdims, cstrides, cbox, false);
    const cuuint64_t odims[3] = {64, 63, IH}, ostrides[2] = {128, IW * 36};
    const cuuint32_t obox[3] = {64, 18, 8};
    make(&tm.off, d_in[1], 3, odims, ostrides, obox, false);
    const cuuint32_t cb[3] = {64, 1, IH};
    make(&tm.col, d_in[1], 3, odims, ostrides, cb, false);
  }
  dcn_kernel<<<GRID, NTHREADS, SMEM_BYTES>>>((const uint4*)d_in[0], (const uint32_t*)d_in[1], (const uint4*)d_in[2], scratch, tsp, 0u, tm);
}
```

```cpp
#include <cuda_runtime.h>
#include <cuda.h>
#include <cuda_bf16.h>
#include <stdint.h>

namespace {

constexpr int IH = 224, IW = 224, IC = 96;
constexpr int GRID = 132, NTHREADS = 512;
constexpr int NI = 60, NR = GRID - NI;
constexpr int SLOT = 9216;
constexpr int SMEM_BYTES = 232448;
constexpr int PLANE = 66 * 64, UNIT = 6 * PLANE;
constexpr int SM_V = 256, SM_X = 8704, SM_W = 36 * PLANE + 512, SM_BAR = SM_W + 8 * SLOT;
constexpr int B_WF = 0, B_WE = 36, B_XF = 60, B_XR = 66, B_ST = 72, B_UR = 80, B_OF = 84, B_OS = 85, B_EP = 86, B_OK = 87, B_G = 88;
constexpr int O_CNT = 832, O_VER = 848, O_EPO = 852, O_LST = 864, O_COR = 1024;
constexpr int MAXEX = 16, EARLY = 128, QUEUE = 192;
constexpr uint32_t FAILED = 255;
constexpr int GSLICE = 144 * 64, SM_GX = 18 * SLOT;
constexpr int SM_RAW = SM_V + 3 * UNIT, SM_OFF = SM_V + 6 * UNIT - 2 * SLOT;
constexpr int YSLICE = 36 * 10 * 64, SM_YX = 16 * SLOT, SM_YT = SM_YX + 3 * YSLICE;
#define PSLEEP 20
#define REDSEM "red.release"
#define XN 3
#define XJ4 3
#define XJ5 7
#define HAND 12
#define PUB1 10
#define TGRP 8
#define TDEP 0
#define TSBON 0
#define YPRMT 1
#define STW 0
#define LATE4 0
#define PW -1
#define TX 0
#define SPACE 2
#define VC 2
#define VGATE 0
#define YLAG 0
#define KEEP 0
#define YP1 3
#define YP2 6
#define MIX 1
#define YORD 1
#define Y0M 0
#define POLLT 4200
#define TS2 1
#define T2N 2
#define PUB0 3
#define GDT 3000
#define SCANB 6
#define OFFAT 3
#define UHOLD 1
#define USTG 1
#define FWT 0
#define EWAIT 1
#define PFLY 1
#define PGAP 150
#define X5W 12
#define WAT 0
#define R2 32
#define SPLITW 0
#define ORD 0
constexpr int RAWT = SPLITW ? 3072 : 6144, RAWC = SPLITW ? 3 * SLOT : 3072;
#define TSX 0
#define BUB 0
#define CPF 0
#define SPF 0
#define UDRY 1
#define U16 1
#define PFP 99
#define PFK 1
#define LOCK 2
#define LOCK0 0
#define LOCKN 7
#define CG 2
#define XT1 1900
#define XT2 3800
#define XDT 900
#define YX0 1400
#define YX1 5000
#define YX2 8500
#define YWT 2500
#define YWDT 1100

struct Scratch {
  uint4 u[16 * SLOT / 16];
  uint4 w[12 * SLOT / 16];
  uint32_t ready[32];
  uint2 req[QUEUE];
  uint2 res[QUEUE][48];
  uint2 mail[GRID][32];
};
__device__ __align__(128) Scratch g_scratch;

#define TSE(i)
#define TSB(i)

__device__ __forceinline__ float bf16lo(uint32_t v) { return __uint_as_float(v << 16); }
__device__ __forceinline__ float bf16hi(uint32_t v) { return __uint_as_float(v & 0xffff0000u); }
__device__ __forceinline__ uint32_t smem_u32(const void* p) { return (uint32_t)__cvta_generic_to_shared(p); }
__device__ __forceinline__ void mbar_init(uint32_t bar, uint32_t count) {
  asm volatile("mbarrier.init.shared::cta.b64 [%0], %1;\n" ::"r"(bar), "r"(count) : "memory");
}
__device__ __forceinline__ void mbar_expect_tx(uint32_t bar, uint32_t bytes) {
  asm volatile("mbarrier.arrive.expect_tx.shared::cta.b64 _, [%0], %1;\n" ::"r"(bar), "r"(bytes) : "memory");
}
__device__ __forceinline__ void mbar_wait(uint32_t bar, uint32_t parity = 0) {
  uint32_t done;
#pragma unroll 1
  for (uint32_t spin = 0; spin < (1u << 22); spin++) {
    asm volatile(
        "{\n.reg .pred p;\n"
        "mbarrier.try_wait.parity.shared::cta.b64 p, [%1], %2;\n"
        "selp.u32 %0, 1, 0, p;\n}\n"
        : "=r"(done)
        : "r"(bar), "r"(parity)
        : "memory");
    if (done) return;
  }
  __trap();
}
__device__ __forceinline__ uint32_t mbar_test(uint32_t bar, uint32_t parity = 0) {
  uint32_t done;
  asm volatile(
      "{\n.reg .pred p;\n"
      "mbarrier.test_wait.parity.shared::cta.b64 p, [%1], %2;\n"
      "selp.u32 %0, 1, 0, p;\n}\n"
      : "=r"(done)
      : "r"(bar), "r"(parity)
      : "memory");
  return done;
}
__device__ __forceinline__ uint32_t clock32() {
  uint32_t c;
  asm volatile("mov.u32 %0, %%clock;\n" : "=r"(c)::"memory");
  return c;
}
__device__ __forceinline__ void wait_until(uint32_t t0, uint32_t dt) {
  while (clock32() - t0 < dt) __nanosleep(50);
}
__device__ __forceinline__ void mbar_wait_cluster(uint32_t bar, uint32_t parity = 0) {
  uint32_t done;
#pragma unroll 1
  for (uint32_t spin = 0; spin < (1u << 22); spin++) {
    asm volatile(
        "{\n.reg .pred p;\n"
        "mbarrier.try_wait.parity.acquire.cluster.shared::cta.b64 p, [%1], %2;\n"
        "selp.u32 %0, 1, 0, p;\n}\n"
        : "=r"(done)
        : "r"(bar), "r"(parity)
        : "memory");
    if (done) return;
  }
  __trap();
}
__device__ __forceinline__ void tma_load_3d(uint32_t dst, const CUtensorMap* tm, uint32_t bar, int c0, int c1, int c2) {
  asm volatile(
      "cp.async.bulk.tensor.3d.shared::cluster.global.mbarrier::complete_tx::bytes [%0], [%1, {%3, %4, %5}], [%2];\n" ::"r"(dst),
      "l"(reinterpret_cast<uint64_t>(tm)), "r"(bar), "r"(c0), "r"(c1), "r"(c2)
      : "memory");
}
__device__ __forceinline__ void tma_load_5d(uint32_t dst, const CUtensorMap* tm, uint32_t bar, int c, int kj, int ki) {
  asm volatile(
      "cp.async.bulk.tensor.5d.shared::cluster.global.mbarrier::complete_tx::bytes [%0], [%1, {%3, %4, %3, %5, %6}], [%2];\n" ::"r"(dst),
      "l"(reinterpret_cast<uint64_t>(tm)), "r"(bar), "r"(0), "r"(c), "r"(kj), "r"(ki)
      : "memory");
}
__device__ __forceinline__ void tma_load_4d(uint32_t dst, const CUtensorMap* tm, uint32_t bar, int c1, int c2, int c3) {
  asm volatile(
      "cp.async.bulk.tensor.4d.shared::cluster.global.mbarrier::complete_tx::bytes [%0], [%1, {%3, %4, %5, %6}], [%2];\n" ::"r"(dst),
      "l"(reinterpret_cast<uint64_t>(tm)), "r"(bar), "r"(0), "r"(c1), "r"(c2), "r"(c3)
      : "memory");
}
__device__ __forceinline__ void tma_load_5t(uint32_t dst, const CUtensorMap* tm, uint32_t bar, int kj, int chunk) {
  asm volatile(
      "cp.async.bulk.tensor.5d.shared::cluster.global.mbarrier::complete_tx::bytes [%0], [%1, {%3, %3, %4, %3, %5}], [%2];\n" ::"r"(dst),
      "l"(reinterpret_cast<uint64_t>(tm)), "r"(bar), "r"(0), "r"(kj), "r"(chunk)
      : "memory");
}
template <int BYTES>
__device__ __forceinline__ void bulk_load(uint32_t dst, const void* src, uint32_t bar) {
  asm volatile("cp.async.bulk.shared::cluster.global.mbarrier::complete_tx::bytes [%0], [%1], %3, [%2];\n" ::"r"(dst), "l"(src),
               "r"(bar), "n"(BYTES)
               : "memory");
}
template <int BYTES>
__device__ __forceinline__ void bulk_store(void* dst, uint32_t src) {
  asm volatile("cp.async.bulk.global.shared::cta.bulk_group [%0], [%1], %2;\n" ::"l"(dst), "r"(src), "n"(BYTES) : "memory");
}
__device__ __forceinline__ void tma_store3(const CUtensorMap* tm, uint32_t src, int c0, int c1, int c2) {
  asm volatile("cp.async.bulk.tensor.3d.global.shared::cta.bulk_group [%0, {%2, %3, %4}], [%1];\n" ::"l"(
                   reinterpret_cast<uint64_t>(tm)),
               "r"(src), "r"(c0), "r"(c1), "r"(c2)
               : "memory");
}
__device__ __forceinline__ void tma_store(const CUtensorMap* tm, uint32_t src, int c1, int c2) {
  asm volatile("cp.async.bulk.tensor.4d.global.shared::cta.bulk_group [%0, {%2, %3, %4, %2}], [%1];\n" ::"l"(
                   reinterpret_cast<uint64_t>(tm)),
               "r"(src), "r"(0), "r"(c1), "r"(c2)
               : "memory");
}
__device__ __forceinline__ uint64_t w_desc(uint32_t saddr) {
  return (uint64_t)((saddr & 0x3FFFF) >> 4) | ((uint64_t)(1024 >> 4) << 16) | ((uint64_t)(512 >> 4) << 32) | ((uint64_t)2 << 62);
}
__device__ __forceinline__ uint64_t a_desc(uint32_t saddr) {
  return (uint64_t)((saddr & 0x3FFFF) >> 4) | ((uint64_t)1 << 16) | ((uint64_t)(512 >> 4) << 32) | ((uint64_t)2 << 62);
}
#define ACC_OPERANDS(c, d)                                                                                        \
  c(d[0]), c(d[1]), c(d[2]), c(d[3]), c(d[4]), c(d[5]), c(d[6]), c(d[7]), c(d[8]),      \
      c(d[9]), c(d[10]), c(d[11]), c(d[12]), c(d[13]), c(d[14]), c(d[15]), c(d[16]),       \
      c(d[17]), c(d[18]), c(d[19]), c(d[20]), c(d[21]), c(d[22]), c(d[23]), c(d[24]),      \
      c(d[25]), c(d[26]), c(d[27]), c(d[28]), c(d[29]), c(d[30]), c(d[31]), c(d[32]),      \
      c(d[33]), c(d[34]), c(d[35]), c(d[36]), c(d[37]), c(d[38]), c(d[39]), c(d[40]),      \
      c(d[41]), c(d[42]), c(d[43]), c(d[44]), c(d[45]), c(d[46]), c(d[47])
#define ACC_LIST                                                                   \
  "{%0, %1, %2, %3, %4, %5, %6, %7, %8, %9, %10, %11, %12, %13, %14, %15, "        \
  "%16, %17, %18, %19, %20, %21, %22, %23, %24, %25, %26, %27, %28, %29, %30, %31, " \
  "%32, %33, %34, %35, %36, %37, %38, %39, %40, %41, %42, %43, %44, %45, %46, %47}, "
__device__ __forceinline__ void wgmma_ss(float* d, uint64_t adesc, uint64_t bdesc, int accumulate = 1) {
  asm volatile(
      "{\n.reg .pred p;\nsetp.ne.b32 p, %50, 0;\n"
      "wgmma.mma_async.sync.aligned.m64n96k16.f32.bf16.bf16 " ACC_LIST "%48, %49, p, 1, 1, 0, 1;\n}\n"
      : ACC_OPERANDS("+f", d)
      : "l"(adesc), "l"(bdesc), "r"(accumulate));
}
__device__ __forceinline__ void wgmma_fence() { asm volatile("wgmma.fence.sync.aligned;\n" ::: "memory"); }
__device__ __forceinline__ void wgmma_commit() { asm volatile("wgmma.commit_group.sync.aligned;\n" ::: "memory"); }
template <int N>
__device__ __forceinline__ void wgmma_wait() { asm volatile("wgmma.wait_group.sync.aligned %0;\n" ::"n"(N) : "memory"); }
__device__ __forceinline__ void acc_fence(float* d) {
#pragma unroll
  for (int i = 0; i < 48; i++) asm volatile("" : "+f"(d[i])::"memory");
}
__device__ __forceinline__ void arrive_if(uint32_t bar) {
  asm volatile("{\n.reg .pred p;\nsetp.ne.u32 p, %0, 0;\n@p mbarrier.arrive.shared::cluster.b64 _, [%0];\n}\n" ::"r"(bar) : "memory");
}
__device__ __forceinline__ void lds128(uint32_t* v, uint32_t addr) {
  asm volatile("ld.shared.v4.b32 {%0, %1, %2, %3}, [%4];\n" : "=r"(v[0]), "=r"(v[1]), "=r"(v[2]), "=r"(v[3]) : "r"(addr) : "memory");
}
__device__ __forceinline__ void sts128(uint32_t addr, const uint32_t* v) {
  asm volatile("st.shared.v4.b32 [%0], {%1, %2, %3, %4};\n" ::"r"(addr), "r"(v[0]), "r"(v[1]), "r"(v[2]), "r"(v[3]) : "memory");
}
__device__ __forceinline__ __nv_bfloat162 as_bf2(uint32_t v) { return *reinterpret_cast<__nv_bfloat162*>(&v); }
__device__ __forceinline__ uint32_t as_u32(__nv_bfloat162 v) { return *reinterpret_cast<uint32_t*>(&v); }
__device__ __forceinline__ uint32_t hfma2(uint32_t a, uint32_t b, uint32_t c) { return as_u32(__hfma2(as_bf2(a), as_bf2(b), as_bf2(c))); }
__device__ __forceinline__ uint32_t pack2(float a, float b) { return as_u32(__floats2bfloat162_rn(a, b)); }
__device__ __forceinline__ bool elect_one() {
  uint32_t r;
  asm volatile("{\n.reg .pred p;\nelect.sync _|p, 0xffffffff;\nselp.u32 %0, 1, 0, p;\n}\n" : "=r"(r));
  return r != 0;
}
__device__ __forceinline__ void wgmma_rs(float* d, const uint32_t* a, uint64_t bdesc, int accumulate = 1) {
  asm volatile(
      "{\n.reg .pred p;\nsetp.ne.b32 p, %53, 0;\n"
      "wgmma.mma_async.sync.aligned.m64n96k16.f32.bf16.bf16 " ACC_LIST "{%48, %49, %50, %51}, %52, p, 1, 1, 1;\n}\n"
      : ACC_OPERANDS("+f", d)
      : "r"(a[0]), "r"(a[1]), "r"(a[2]), "r"(a[3]), "l"(bdesc), "r"(accumulate));
}
__device__ __forceinline__ void ldsm4(uint32_t* r, uint32_t addr) {
  asm volatile("ldmatrix.sync.aligned.m8n8.x4.shared.b16 {%0, %1, %2, %3}, [%4];\n"
               : "=r"(r[0]), "=r"(r[1]), "=r"(r[2]), "=r"(r[3])
               : "r"(addr)
               : "memory");
}
__device__ __forceinline__ void lds64(uint32_t* v, uint32_t addr) {
  asm volatile("ld.shared.v2.b32 {%0, %1}, [%2];\n" : "=r"(v[0]), "=r"(v[1]) : "r"(addr) : "memory");
}
__device__ __forceinline__ void sts64(uint32_t addr, uint32_t a, uint32_t b) {
  asm volatile("st.shared.v2.b32 [%0], {%1, %2};\n" ::"r"(addr), "r"(a), "r"(b) : "memory");
}
__device__ __forceinline__ void sts32(uint32_t addr, uint32_t v) {
  asm volatile("st.shared.u32 [%0], %1;\n" ::"r"(addr), "r"(v) : "memory");
}
__device__ __forceinline__ uint32_t hadd2(uint32_t a, uint32_t b) { return as_u32(__hadd2(as_bf2(a), as_bf2(b))); }
__device__ __forceinline__ uint32_t hsub2(uint32_t a, uint32_t b) { return as_u32(__hsub2(as_bf2(a), as_bf2(b))); }
__device__ __forceinline__ uint32_t hmin2(uint32_t a, uint32_t b) { return as_u32(__hmin2(as_bf2(a), as_bf2(b))); }
__device__ __forceinline__ uint32_t hmax2(uint32_t a, uint32_t b) { return as_u32(__hmax2(as_bf2(a), as_bf2(b))); }
__device__ __forceinline__ uint32_t hfma2_lo(uint32_t w, uint32_t a, uint32_t c) {
  return as_u32(__hfma2(__low2bfloat162(as_bf2(w)), as_bf2(a), as_bf2(c)));
}
__device__ __forceinline__ uint32_t hfma2_hi(uint32_t w, uint32_t a, uint32_t c) {
  return as_u32(__hfma2(__high2bfloat162(as_bf2(w)), as_bf2(a), as_bf2(c)));
}
__device__ __forceinline__ uint32_t prmt(uint32_t a, uint32_t b, uint32_t sel) {
  uint32_t r;
  asm("prmt.b32 %0, %1, %2, %3;\n" : "=r"(r) : "r"(a), "r"(b), "r"(sel));
  return r;
}
__device__ __forceinline__ constexpr uint32_t tap_delta(int a, int b) {
  return (a == 0 ? 0xbf80u : a == 1 ? 0u : 0x3f80u) | (b == 0 ? 0xbf800000u : b == 1 ? 0u : 0x3f800000u);
}
__device__ __forceinline__ int thread_id() {
  int t;
  asm volatile("mov.u32 %0, %%tid.x;\n" : "=r"(t));
  return t;
}
__device__ __forceinline__ void proxy_fence() { asm volatile("fence.proxy.async.shared::cta;\n" ::: "memory"); }
template <int PITCH>
__device__ __forceinline__ void stage16(const float* acc, int jp, uint32_t stg) {
  uint32_t pk[4];
#pragma unroll
  for (int i = 0; i < 4; i++) pk[i] = pack2(acc[jp * 8 + i * 2], acc[jp * 8 + i * 2 + 1]);
  asm volatile("stmatrix.sync.aligned.m8n8.x4.shared.b16 [%0], {%1, %2, %3, %4};\n" ::"r"((stg ^ ((jp & 1) * 32)) + (jp >> 1) * PITCH),
               "r"(pk[0]), "r"(pk[1]), "r"(pk[2]), "r"(pk[3])
               : "memory");
}
__device__ __forceinline__ uint32_t swz(uint32_t a, uint32_t chunk) { return a | (((chunk ^ (a >> 7)) & 3) << 4); }
__device__ __forceinline__ void fma_ip(float& d, float c, float a) { asm volatile("fma.rn.f32 %0, %1, %2, %0;\n" : "+f"(d) : "f"(c), "f"(a)); }
__device__ __forceinline__ void fma_sc(float& d, float c, float a) { asm volatile("fma.rn.f32 %0, %1, %0, %2;\n" : "+f"(d) : "f"(c), "f"(a)); }

__device__ __forceinline__ void v_load(uint32_t (*d)[2], const uint32_t* a, uint32_t a5, uint32_t off) {
#pragma unroll
  for (int j = 0; j < 6; j++) lds64(d[j], (j == 5 ? a5 : a[j & 3]) + (j >> 2) * 4 * PLANE + off);
}
__device__ __forceinline__ void v_store(uint32_t (*d)[2], const uint32_t* a, uint32_t o05, uint32_t o34, uint32_t off) {
#pragma unroll
  for (int i = 0; i < 2; i++)
    asm volatile(
        "{\n.reg .b32 p, q, r, c;\n"
        "add.rn.bf16x2 %0, %0, %4;\n"
        "add.rn.bf16x2 %5, %5, %1;\n"
        "mov.b32 c, 0xc080c080;\n"
        "fma.rn.bf16x2 p, c, %2, %4;\n"
        "fma.rn.bf16x2 q, c, %1, %3;\n"
        "mov.b32 c, 0xc088c088;\n"
        "fma.rn.bf16x2 %0, c, %2, %0;\n"
        "fma.rn.bf16x2 %5, c, %3, %5;\n"
        "mov.b32 c, 0xbe80be80;\n"
        "fma.rn.bf16x2 r, c, %2, %4;\n"
        "fma.rn.bf16x2 %3, c, %1, %3;\n"
        "mov.b32 c, 0x3f003f00;\n"
        "fma.rn.bf16x2 %1, c, q, p;\n"
        "mov.b32 c, 0xbf00bf00;\n"
        "fma.rn.bf16x2 %2, c, q, p;\n"
        "mov.b32 c, 0x40004000;\n"
        "fma.rn.bf16x2 %4, c, %3, r;\n"
        "mov.b32 c, 0xc000c000;\n"
        "fma.rn.bf16x2 %3, c, %3, r;\n}\n"
        : "+r"(d[0][i]), "+r"(d[1][i]), "+r"(d[2][i]), "+r"(d[3][i]), "+r"(d[4][i]), "+r"(d[5][i]));
  sts64(a[0] + o05 + off, d[0][0], d[0][1]);
  sts64(a[1] + o05 + off, d[5][0], d[5][1]);
  sts64(a[2] + off, d[1][0], d[1][1]);
  sts64(a[3] + off, d[2][0], d[2][1]);
  sts64(a[0] + o34 + off, d[4][0], d[4][1]);
  sts64(a[1] + o34 + off, d[3][0], d[3][1]);
}
__device__ __forceinline__ void u_math16(const uint32_t (*g)[4], uint32_t dst) {
#pragma unroll
  for (int h = 0; h < 2; h++) {
    uint32_t u[2][4];
#pragma unroll
    for (int i = 0; i < 4; i++) {
      const uint32_t s = hfma2(0x3e803e80u, g[2 - h * 2][i], g[h * 2][i]);
      u[0][i] = hfma2(0x3f003f00u, g[1][i], s);
      u[1][i] = hfma2(0xbf00bf00u, g[1][i], s);
    }
    sts128(dst + h * 2 * SLOT, u[0]);
    sts128(dst + (h * 2 + 1) * SLOT, u[1]);
  }
}
__device__ __forceinline__ uint32_t u_src(int t) {
  const int c = t >= 576, q = t - c * 576, b = q >> 6, kj = (b * 11) >> 5;
  return SM_RAW + c * RAWC + kj * (RAWT - 192) + b * 64 + ((q >> 2) & 15) * 192 + (q & 3) * 16;
}
__device__ __forceinline__ uint32_t u_dst(int t) { return SM_W + (t >= 576 ? 3 * SLOT : 0) + (t ^ ((t >> 3) & 3)) * 16; }

__device__ __forceinline__ void ldg128(uint32_t* v, const uint4* p) {
  asm volatile("ld.global.nc.v4.b32 {%0, %1, %2, %3}, [%4];\n" : "=r"(v[0]), "=r"(v[1]), "=r"(v[2]), "=r"(v[3]) : "l"(p));
}
__device__ __forceinline__ uint32_t lds32(uint32_t addr) {
  uint32_t v;
  asm volatile("ld.shared.u32 %0, [%1];\n" : "=r"(v) : "r"(addr) : "memory");
  return v;
}
__device__ __forceinline__ void ldsm4_if(uint32_t* r, uint32_t addr, uint32_t on) {
  asm volatile(
      "{\n.reg .pred p;\nsetp.ne.u32 p, %5, 0;\n"
      "@p ldmatrix.sync.aligned.m8n8.x4.shared.b16 {%0, %1, %2, %3}, [%4];\n}\n"
      : "+r"(r[0]), "+r"(r[1]), "+r"(r[2]), "+r"(r[3])
      : "r"(addr), "r"(on)
      : "memory");
}
__device__ __forceinline__ uint32_t hmul2_lo(uint32_t w, uint32_t a) { return as_u32(__hmul2(__low2bfloat162(as_bf2(w)), as_bf2(a))); }
__device__ __forceinline__ uint32_t clip2(uint32_t p) { return hmin2(hmax2(p, 0u), 0x435f435fu); }
__device__ __forceinline__ uint32_t frac2(uint32_t pos) {
  const float py = bf16lo(pos), px = bf16hi(pos);
  return __byte_perm(__float_as_uint(py - floorf(py)), __float_as_uint(px - floorf(px)), 0x7632);
}
__device__ __forceinline__ void coefs(uint32_t w, uint32_t& p0, uint32_t& p1) {
  const uint32_t o = hsub2(0x3f803f80u, w), xa = __byte_perm(o, w, 0x7632);
  p0 = hmul2_lo(o, xa);
  p1 = hmul2_lo(w, xa);
}
__device__ __forceinline__ uint32_t blend(uint32_t p0, uint32_t p1, uint32_t t, uint32_t g, uint32_t h, uint32_t k) {
  return hfma2_hi(p1, k, hfma2_lo(p1, h, hfma2_hi(p0, g, hmul2_lo(p0, t))));
}
__device__ __forceinline__ void st_pair(uint2* p, uint32_t a, uint32_t b) {
  asm volatile("st.relaxed.gpu.global.v2.u32 [%0], {%1, %2};\n" ::"l"(p), "r"(a), "r"(b) : "memory");
}
__device__ __forceinline__ void ld_pair(uint32_t* v, const uint2* p) {
  asm volatile("ld.relaxed.gpu.global.v2.u32 {%0, %1}, [%2];\n" : "=r"(v[0]), "=r"(v[1]) : "l"(p) : "memory");
}
__device__ __forceinline__ uint32_t request(Scratch* scr, uint32_t slot, uint32_t pos, int h, int w, int tap) {
  if (slot < QUEUE) st_pair(scr->req + slot, pos, 0x80000000u | (h << 12) | (w << 4) | tap);
  return slot;
}
__device__ __forceinline__ uint32_t count_up(uint32_t addr) {
  uint32_t i;
  asm volatile("atom.shared.add.u32 %0, [%1], 1;\n" : "=r"(i) : "r"(addr) : "memory");
  return i;
}
__device__ __forceinline__ void patch(uint32_t id, uint32_t id0, uint32_t n, uint32_t base, uint32_t pitch, uint32_t ctl, int lane) {
  uint32_t todo = __ballot_sync(0xffffffffu, id - id0 < n);
  if (!todo) return;
#pragma unroll 1
  do {
    const int i0 = __ffs(todo) - 1;
    todo &= todo - 1;
    const uint32_t p0 = __shfl_sync(0xffffffffu, id, i0), other = todo & __ballot_sync(0xffffffffu, id != p0);
    const int i1 = __ffs(other) - 1;
    todo &= ~(other & -other);
    const uint32_t p1 = __shfl_sync(0xffffffffu, id, i1);
    if ((lane & 15) < 12 && (lane < 16 || other)) {
      const uint32_t a = swz(base + ((lane >> 2) & 3) * pitch + ((lane < 16 ? p0 : p1) - id0) * 64, lane);
      uint32_t v[4], c[4];
      lds128(v, a);
      lds128(c, ctl + O_COR + (lane < 16 ? i0 : i1) * 192 + (lane & 15) * 16);
#pragma unroll
      for (int k = 0; k < 4; k++) v[k] = hadd2(v[k], c[k]);
      sts128(a, v);
    }
    __syncwarp();
  } while (todo);
  proxy_fence();
  __syncwarp();
}

struct Maps {
  CUtensorMap x, xp, w, wh, wc, out, off, col, gx, gout;
  CUtensorMap bx[2], bw[2], bout[2];
};

__global__ void __launch_bounds__(NTHREADS, 1)
dcn_kernel(const uint4* __restrict__ x, const uint32_t* __restrict__ offs, const uint4* __restrict__ wgt, Scratch* __restrict__ scr, uint32_t* tsp, const uint32_t never,
           const __grid_constant__ Maps tm) {
  extern __shared__ __align__(1024) uint8_t smem[];
  constexpr uint32_t sbase = 1024;
  constexpr uint32_t bars = sbase + SM_BAR;
  const int tid = threadIdx.x;
  const int bk = blockIdx.x >> 1;
  const int cta = MIX ? (blockIdx.x & 1 ? (bk < 4 ? bk + 56 : bk < 60 ? bk - 4 : bk + 66) : bk + 60) : blockIdx.x;
  const uint32_t tstart = clock32();
  const int wid = __shfl_sync(0xffffffffu, tid >> 5, 0);
  const int lane = tid & 31;
  const int ri = cta - NI, ry = ri / 3, x0 = 32 + (ri - ry * 3) * 64, y0 = 32 + ry * 8;
  const int band = cta >= 24, g0 = 32 + (cta - band * 24) * 8;
  if (wid == 12 && cta >= NI) {
    if (elect_one()) {
      mbar_init(bars + (B_WF + 1) * 8, 1);
      if (SPLITW) mbar_init(bars + (B_WF + 2) * 8, 1);
      mbar_init(bars + B_XF * 8, 1);
      asm volatile("fence.mbarrier_init.release.cluster;\n" ::: "memory");
      mbar_expect_tx(bars + (B_WF + 1) * 8, SPLITW ? 3 * SLOT : 6 * SLOT);
      if (SPLITW) mbar_expect_tx(bars + (B_WF + 2) * 8, 3 * SLOT);
      mbar_expect_tx(bars + B_XF * 8, UNIT);
      tma_load_3d(sbase + SM_RAW, SPLITW ? &tm.wh : &tm.w, bars + (B_WF + 1) * 8, 0, 0, 0);
      if (SPLITW == 1 && !ORD) tma_load_3d(sbase + SM_RAW + RAWC, &tm.wh, bars + (B_WF + 2) * 8, 0, 24, 0);
      tma_load_3d(sbase + SM_V, &tm.x, bars + B_XF * 8, 0, x0 - 1, y0 + (ry & 1) * 4 - 1);
      if (SPLITW == 1 && ORD) tma_load_3d(sbase + SM_RAW + RAWC, &tm.wh, bars + (B_WF + 2) * 8, 0, 24, 0);
    }
    asm volatile("bar.arrive 0, 512;\n" ::: "memory");
  }
  if (wid == 12 && cta < NI - 4) {
    if (elect_one() && cta < 48) {
      mbar_init(bars + B_WF * 8, 1);
      mbar_init(bars + B_XF * 8, 1);
      asm volatile("fence.mbarrier_init.release.cluster;\n" ::: "memory");
      mbar_expect_tx(bars + B_WF * 8, 2 * SLOT);
      mbar_expect_tx(bars + B_XF * 8, YSLICE);
      while (clock32() - tstart < YX0) {}
      if (YORD) tma_load_3d(sbase + SM_YX, &tm.bx[band], bars + B_XF * 8, 0, g0 - 1, -2);
      tma_load_5d(sbase, &tm.bw[band], bars + B_WF * 8, 0, 0, 0);
      tma_load_5d(sbase + SLOT, &tm.bw[band], bars + B_WF * 8, 16, 0, 0);
      if (!YORD) tma_load_3d(sbase + SM_YX, &tm.bx[band], bars + B_XF * 8, 0, g0 - 1, -2);
    }
    asm volatile("bar.arrive 0, 512;\n" ::: "memory");
  }
  if (wid == 12 && cta >= NI - 4 && cta < NI) {
    if (elect_one()) {
#pragma unroll
      for (int c = 0; c < 5; c++) mbar_init(bars + c * 8, 1);
      asm volatile("fence.mbarrier_init.release.cluster;\n" ::: "memory");
    }
    asm volatile("bar.arrive 0, 512;\n" ::: "memory");
    if (elect_one()) {
      if (cta < NI - 1) {
#pragma unroll
        for (int c = 0; c < 4; c++) {
          mbar_expect_tx(bars + c * 8, SLOT);
          tma_load_4d(sbase + (18 + c) * SLOT, &tm.wc, bars + c * 8, (c + 2) * 24, cta - (NI - 4), 0);
        }
      } else {
        mbar_expect_tx(bars + 3 * 8, 28672 + 16128);
        tma_load_3d(sbase + 18 * SLOT, &tm.col, bars + 3 * 8, 0, 9, 0);
        bulk_load<16128>(sbase + 18 * SLOT + 28672, offs + 32 * IW * 9, bars + 3 * 8);

      }
    }
  }
  const int f = wid * 4 + (lane >> 3), g = g0 + (lane & 7);
  uint32_t o9[9];
  if (cta < 48 && wid < 8) {
    const uint32_t* op = offs + (band ? g * IW + f : f * IW + g) * 9;
#pragma unroll
    for (int a = 0; a < 3; a++)
#pragma unroll
      for (int b = 0; b < 3; b++) o9[a * 3 + b] = __ldg(op + (band ? b * 3 + a : a * 3 + b));
  }
  if (cta >= 48 && cta < NI - 4 && tid < 36) asm volatile("prefetch.global.L2 [%0];\n" ::"l"(offs + ((cta & 7) * 4 + tid / 9) * IW * 9 + tid % 9 * 32));
  if (cta >= NI - 4 && cta < NI) {
    const int kj = cta - (NI - 4);
    if (wid != 12) asm volatile("bar.sync 0, 512;\n" ::: "memory");
    auto get_epoch = [&]() {
      uint32_t e;
      asm volatile("ld.relaxed.gpu.global.u32 %0, [%1];\n" : "=r"(e) : "l"(scr->ready + (kj == 3 ? 3 : 2)) : "memory");
      return (e & ~127u) + 128;
    };
    uint32_t epoch;
    auto load_w = [&]() {
      mbar_expect_tx(bars + 4 * 8, 18 * SLOT);
#pragma unroll
      for (int sl = 0; sl < 3; sl++) tma_load_3d(sbase + sl * 6 * SLOT, &tm.w, bars + 4 * 8, 0, sl * 48, 0);
    };
    if (kj == 3) {
      constexpr uint32_t src = sbase + 18 * SLOT, lst = src + 28672 + 16128;
      uint32_t big = 0;
      epoch = get_epoch();
      if (tid < GRID) sts32(bars + 64 + tid * 4, 0);
      __syncthreads();
      if (tid == 0) load_w();
      mbar_wait(bars + 3 * 8);
#pragma unroll
      for (int i = 0; i < 6; i++) {
        const uint32_t p = tid + i * 512;
        uint32_t v[4];
        lds128(v, src + p * 16);
        const uint32_t lim = i == 0 && tid < 256 ? 0x42804080u : i >= 3 && (p - 1792 < 72 || p - 2296 < 72) ? 0x40804280u : 0x42804280u;
        uint32_t over = 0;
#pragma unroll
        for (int k = 0; k < 4; k++) over |= (v[k] & 0x7fff7fffu) + lim;
        if ((over & 0x80008000u) && (p < 1792 ? (tid & 7) < 5 : p < 2800)) big |= 1u << i;
      }
#pragma unroll 1
      for (; big; big &= big - 1) {
        const uint32_t i = count_up(bars + 64 + 57 * 4);
        if (i < 1024) sts32(lst + i * 4, tid + (__ffs(big) - 1) * 512);
      }
      __syncthreads();
      const uint32_t n = lds32(bars + 64 + 57 * 4);
      if (n > 1024 && tid < GRID && (tid < 56 || tid >= NI)) sts32(bars + 64 + tid * 4, FAILED);
#pragma unroll 1
      for (uint32_t c = tid; c < n * 4 && n <= 1024; c += 512) {
        const uint32_t wq = lds32(lst + (c & ~3u)) * 4 + (c & 3), col = wq < 7168;
        const uint32_t wi = col ? wq & 31 : wq - 7168, px = (wi * 7282) >> 16, tap = wi - px * 9;
        const int eh = col ? wq >> 5 : 32 + (px >= 224), ew = col ? 32 + px : px >= 224 ? px - 224 : px, ki = (tap * 11) >> 5;
        const uint32_t gp = pack2((float)(eh + ki - 1), (float)(ew + (int)tap - ki * 3 - 1));
        const uint32_t pos = clip2(hadd2(gp, lds32(src + wq * 4)));
        const uint32_t d = __byte_perm(hsub2(pos, hmin2(gp, 0x435f435fu)), 0, ew < 32 ? 0x1032 : 0x3210) & 0x7fff7fffu;
        if (d <= (min(eh, ew) < 32 ? 0x3f80u : 0u) || (col && (px >= 2 || eh >> 1 == 16))) continue;
        const int client = eh < 32 ? 0 : ew < 32 ? 24 : NI + ((eh - 32) >> 3) * 3 + ((ew - 32) >> 6);
        const uint32_t i = count_up(bars + 64 + client * 4);
        if (i >= MAXEX) continue;
        const uint32_t slot = count_up(bars + 64 + 56 * 4);
        const uint32_t id = eh < 32 ? eh * 8 + ew - 32 : ew < 32 ? ew * 8 + eh - 32 : (eh & 7) * 64 + ((ew - 32) & 63);
        st_pair(scr->mail[client] + i, id | (request(scr, slot < EARLY ? slot : QUEUE, pos, eh, ew, tap) << 16), epoch);
      }
      __syncthreads();
      if (tid < GRID) st_pair(scr->mail[tid] + MAXEX, lds32(bars + 64 + tid * 4), epoch);
      if (tid == 0) {
        scr->ready[3] = epoch;
        scr->ready[8 + ((epoch >> 7) & 1 ^ 1)] = 0;
      }
      TSE(2);
    } else if (wid < 12) {
      const int half = wid >= 6, q = tid - half * 192;
      const uint32_t lin = (q >> 6) * 64 + ((q >> 2) & 15) * 192 + (q & 3) * 16;
      const int e = kj * 192 + (q ^ ((q >> 3) & 3));
      uint32_t ta0 = 0, tb0 = 0, tc0 = 0;
#pragma unroll 1
      for (int c = half - 2 * UDRY; c < 4; c += 2) {
        uint4 g[3], u[4];
        const uint32_t ta = clock32();
        if (c >= 0) mbar_wait(bars + c * 8);
        const uint32_t tb = clock32();
#pragma unroll
        for (int k = 0; k < 3; k++) lds128(&g[k].x, sbase + (18 + c) * SLOT + k * 3072 + lin);
#pragma unroll
        for (int i = 0; i < 4; i++) {
          if (U16) {
            const uint32_t s = hfma2(0x3e803e80u, (&g[2].x)[i], (&g[0].x)[i]), t = hfma2(0x3e803e80u, (&g[0].x)[i], (&g[2].x)[i]);
            (&u[0].x)[i] = hfma2(0x3f003f00u, (&g[1].x)[i], s);
            (&u[1].x)[i] = hfma2(0xbf00bf00u, (&g[1].x)[i], s);
            (&u[2].x)[i] = hfma2(0x3f003f00u, (&g[1].x)[i], t);
            (&u[3].x)[i] = hfma2(0xbf00bf00u, (&g[1].x)[i], t);
          } else {
          float o[4][2];
#pragma unroll
          for (int e = 0; e < 2; e++) {
            const float a = e ? bf16hi((&g[0].x)[i]) : bf16lo((&g[0].x)[i]), bb = e ? bf16hi((&g[1].x)[i]) : bf16lo((&g[1].x)[i]);
            const float cc = e ? bf16hi((&g[2].x)[i]) : bf16lo((&g[2].x)[i]);
            const float s = fmaf(0.25f, cc, a), t = fmaf(0.25f, a, cc);
            o[0][e] = fmaf(0.5f, bb, s);
            o[1][e] = fmaf(-0.5f, bb, s);
            o[2][e] = fmaf(0.5f, bb, t);
            o[3][e] = fmaf(-0.5f, bb, t);
          }
#pragma unroll
          for (int k = 0; k < 4; k++) (&u[k].x)[i] = pack2(o[k][0], o[k][1]);
          }
        }
        if (c >= 2) asm volatile("bar.sync 2, 416;\n" ::: "memory");
#pragma unroll
        for (int k = 0; k < 4; k++)
          asm volatile("{\n.reg .pred p;\nsetp.ge.s32 p, %5, 0;\n@p st.global.v4.b32 [%0], {%1, %2, %3, %4};\n}\n" ::"l"(scr->u + (c * 4 + k) * 576 + e),
                       "r"(u[k].x), "r"(u[k].y), "r"(u[k].z), "r"(u[k].w), "r"(c) : "memory");
        if (c >= 0) asm volatile("bar.arrive 1, 416;\n" ::: "memory");
      }
      epoch = get_epoch();
      if (!half) {
        mbar_wait(bars + 4 * 8);
#pragma unroll 6
        for (int c = 0; c < 12; c++) {
          uint4 v;
          lds128(&v.x, sbase + (c % 6 >> 1) * 6 * SLOT + (c / 6 * 6 + kj) * 6144 + (c & 1) * 3072 + lin);
          scr->w[c * 576 + e] = v;
        }
      }
      asm volatile("bar.arrive 3, %0;\n" ::"r"(512 + (epoch & never)) : "memory");
    } else if (wid == 12) {
      epoch = get_epoch();
#pragma unroll 1
      for (int r = 0; r < 3; r++) {
        asm volatile("bar.sync %0, %1;\n" ::"r"(r < 2 ? 1 : 3), "r"((r < 2 ? 416 : 512) + (epoch & never)) : "memory");
        if (elect_one()) {
          asm volatile("red.release.gpu.global.add.u32 [%0], %1;\n" ::"l"(scr->ready + r), "r"(kj ? 32 : 64) : "memory");
          if (r == WAT) load_w();
          TSE(8 + r);
        }
        __syncwarp();
        if (r == 0) asm volatile("bar.arrive 2, 416;\n" ::: "memory");
      }
    } else {
      epoch = get_epoch();
      asm volatile("bar.arrive 3, %0;\n" ::"r"(512 + (epoch & never)) : "memory");
    }
    const uint32_t dl = sbase + 18 * SLOT + 4 * 12288 + wid * 384;
#pragma unroll 1
    for (int slot = (wid == 12 ? 15 : wid > 12 ? 15 - wid : 14 - wid) * 4 + (kj ^ 3); slot < QUEUE; slot += 64) {
      uint2 rq;
#pragma unroll 1
      for (uint32_t spin = 0;; spin++) {
        uint32_t done[2];
        ld_pair(&rq.x, scr->req + slot);
        if (slot < EARLY) {
          ld_pair(done, scr->mail[56] + MAXEX);
          if (rq.y || (done[1] == epoch && slot >= done[0])) break;
        } else {
          asm volatile("ld.acquire.gpu.global.u32 %0, [%1];\n" : "=r"(done[1]) : "l"(scr->ready + 6) : "memory");
          if (rq.y) break;
          if (done[1] == epoch) {
            asm volatile("ld.relaxed.gpu.global.u32 %0, [%1];\n" : "=r"(done[0]) : "l"(scr->ready + 8 + ((epoch >> 7) & 1)) : "memory");
            if (slot - EARLY >= done[0]) break;
          }
        }
        if (spin > (1u << 22)) __trap();
        __nanosleep(100);
      }
      if (!rq.y) continue;
      __syncwarp();
      TSE(4);
      if (lane == 0) scr->req[slot] = make_uint2(0, 0);
      const int tap = rq.y & 15, ki = (tap * 11) >> 5, gy = (int)bf16lo(rq.x), gx = (int)bf16hi(rq.x);
      const int cy = min(max((int)((rq.y >> 12) & 255) + ki - 1, 0), IH - 1), cx = min(max((int)((rq.y >> 4) & 255) + tap - ki * 3 - 1, 0), IW - 1);
      if (lane < 24) {
        const uint2* pc = reinterpret_cast<const uint2*>(x) + lane;
        const int p = (gy * IW + gx) * 24, sx = gx < IW - 1 ? 24 : 0, sy = gy < IH - 1 ? IW * 24 : 0;
        const uint2 v0 = __ldg(pc + p), v1 = __ldg(pc + p + sx), v2 = __ldg(pc + p + sy), v3 = __ldg(pc + p + sy + sx);
        const uint2 c = __ldg(pc + (cy * IW + cx) * 24);
        uint32_t q0, q1;
        coefs(frac2(rq.x), q0, q1);
        const uint32_t d0 = hsub2(blend(q0, q1, v0.x, v1.x, v2.x, v3.x), c.x), d1 = hsub2(blend(q0, q1, v0.y, v1.y, v2.y, v3.y), c.y);
        const uint32_t dd[4] = {__byte_perm(d0, 0, 0x1010), __byte_perm(d0, 0, 0x3232), __byte_perm(d1, 0, 0x1010), __byte_perm(d1, 0, 0x3232)};
        sts128(dl + lane * 16, dd);
      }
      __syncwarp();
      TSE(5);
      mbar_wait(bars + 4 * 8);
      TSE(6);
      float sum[8] = {};
      const int l24 = min(lane, 23);
#pragma unroll 1
      for (int b = 0; b < 6; b++) {
        uint32_t part[4] = {};
#pragma unroll
        for (int i = 0; i < 8; i++) {
          uint32_t wv[4];
          lds128(wv, sbase + (b >> 1) * 6 * SLOT + tap * 6144 + (b & 1) * 3072 + i * 384 + l24 * 16);
          const uint32_t d = lds32(dl + (b * 16 + i * 2 + (l24 >= 12)) * 4);
#pragma unroll
          for (int k = 0; k < 4; k++) part[k] = hfma2(d, wv[k], part[k]);
        }
#pragma unroll
        for (int k = 0; k < 4; k++) {
          sum[k * 2] += bf16lo(part[k]);
          sum[k * 2 + 1] += bf16hi(part[k]);
        }
      }
#pragma unroll
      for (int k = 0; k < 8; k++) sum[k] += __shfl_down_sync(0xffffffffu, sum[k], 12);
      if (lane < 12) {
#pragma unroll
        for (int k = 0; k < 4; k++)
          asm volatile("st.relaxed.gpu.global.v2.u32 [%0], {%1, %2};\n" ::"l"(scr->res[slot] + lane * 4 + k), "r"(pack2(sum[k * 2], sum[k * 2 + 1])), "r"(epoch) : "memory");
      }
      TSE(1);
    }
    mbar_wait(bars + 4 * 8);
  } else if (wid < 8) {
    const int wg = wid >> 2, warp = wid & 3;
    if (cta < 48) {
    uint32_t cf[36];
#pragma unroll
    for (int i = 0; i < 9; i++) cf[i] = o9[i];
    asm volatile("bar.sync 0, 512;\n" ::: "memory");
    {
      const uint32_t base = pack2((float)f, (float)g), sel = band ? 0x1032u : 0x3210u;
      const uint32_t tab = sbase + SM_YT + wid * 1152;
      uint32_t bad = 0;
#pragma unroll
      for (int a = 0; a < 3; a++)
#pragma unroll
        for (int b = 0; b < 3; b++) {
          const uint32_t gp = hadd2(base, tap_delta(a, b));
          const uint32_t pos = hmin2(hmax2(hadd2(gp, __byte_perm(cf[a * 3 + b], 0, sel)), 0u), 0x435f435fu);
          uint32_t d = hsub2(pos, hmin2(gp, 0x435f435fu));
          if ((d & 0x7fff7fffu) > 0x3f80u) {
            bad = 1;
            d = a == 0 && f == 0 ? 0x3f80u : 0u;
          }
          sts32(tab + (lane & 7) * 144 + (b * 12 + (lane >> 3) * 3 + a) * 4, YPRMT ? (d << 16) | (d & 0x8000u ? 0x3210u : 0x7654u) : hmin2(hmax2(__byte_perm(d, 0, 0x1010), 0x0000ff80u), 0x7f800000u));
        }
      if (bad && g >= 34) sts32(bars + O_CNT, FAILED);
      __syncwarp();
      arrive_if(lane == 0 ? bars + B_OS * 8 : 0u);
      asm volatile("setmaxnreg.inc.sync.aligned.u32 224;\n");
      __syncwarp();
#pragma unroll
      for (int i = 0; i < 9; i++) lds128(cf + i * 4, tab + (lane >> 2) * 144 + i * 16);
    }
    uint32_t xa[3];
#pragma unroll
    for (int b = 0; b < 3; b++)
      xa[b] = swz(sbase + SM_YX + ((wid * 4 + (lane >> 4)) * 10 + min((lane & 7) + b, IW - g0)) * 64, (lane >> 3) & 1);
    float acc[2][48];
    uint32_t X[2][16], A[2][12];
    auto fetch = [&](uint32_t* r, uint32_t a) {
#pragma unroll
      for (int i = 0; i < 4; i++) ldsm4(r + i * 4, (a ^ ((i & 1) * 32)) + i * 1280);
    };
    uint64_t bd = w_desc(sbase);
    uint32_t wf = bars + B_WF * 8;
    mbar_wait(bars + B_XF * 8);
    if (YLAG && wg) { const uint32_t t1 = clock32(); wait_until(t1, YLAG); }
    TSE(0);
    fetch(X[0], xa[0]);
    mbar_wait(wf);
#pragma unroll 1
    for (int s = 0; s < 3; s++) {
#pragma unroll
      for (int n = 0; n < 6; n++) {
        const int b = n >> 1;
        if (n == 5) {
          mbar_wait(bars + (B_XF + min(s + 1, 2)) * 8);
#pragma unroll
          for (int k = 0; k < 3; k++) xa[k] += s < 2 ? YSLICE : 0;
        }
        fetch(X[~n & 1], xa[(n + 1) % 6 >> 1] ^ ((~n & 1) * 32));
        const uint32_t* xr = X[n & 1];
        uint32_t D[7][2];
#pragma unroll
        for (int j = 0; j < 7; j++)
#pragma unroll
          for (int e = 0; e < 2; e++) D[j][e] = hsub2(xr[(j + 1) * 2 + e], xr[j * 2 + e]);
#pragma unroll
        for (int t = 0; t < 2; t++) {
          wgmma_wait<1>();
#pragma unroll
          for (int a = 0; a < 3; a++)
#pragma unroll
            for (int i = 0; i < 4; i++) {
              const int o = t * 2 + (i & 1), e = i >> 1, j = o + a + 1;
              const uint32_t c = cf[b * 12 + o * 3 + a];
              A[t][a * 4 + i] = YPRMT ? hfma2_hi(c, prmt(D[j - 1][e], D[j][e], c), xr[j * 2 + e]) : hfma2_hi(c, D[j][e], hfma2_lo(c, D[j - 1][e], xr[j * 2 + e]));
            }
          wgmma_fence();
#pragma unroll
          for (int a = 0; a < 3; a++) wgmma_rs(acc[t], A[t] + a * 4, bd + n * (SLOT >> 4) + a * 192, (n | a) ? 1 : s);
          wgmma_commit();
        }
        if (n & 1) mbar_wait(wf + (b + 1) * 8);
        if (n & 1) TSB(10 + s * 3 + b);
        if (n == 1 && s == 1 && elect_one()) arrive_if(bars + B_WE * 8);
      }
      bd += 6 * SLOT >> 4;
      wf += 24;
    }
    TSE(1);
    const int lane = thread_id() & 31;
    const uint32_t stg = sbase + wg * 3 * SLOT + (wid & 3) * 2048 + (lane & 15) * 64 + ((((lane >> 4) ^ (lane >> 1)) & 3) << 4);
    wgmma_wait<1>();
    acc_fence(acc[0]);
#pragma unroll
    for (int jp = 0; jp < 6; jp++) stage16<8192>(acc[0], jp, stg);
    wgmma_wait<0>();
    acc_fence(acc[1]);
#pragma unroll
    for (int jp = 0; jp < 6; jp++) stage16<8192>(acc[1], jp, stg + 1024);
    proxy_fence();
    __syncwarp();
    arrive_if(lane == 0 ? bars + (B_ST + wg * 4) * 8 : 0u);
    } else if (cta < NI) {
      asm volatile("bar.sync 0, 512;\n" ::: "memory");
      asm volatile("setmaxnreg.inc.sync.aligned.u32 224;\n");
    } else {
    {
      uint32_t g[3][3][4], src[3], dst[3];
#pragma unroll
      for (int r = 0; r < 3; r++) {
        src[r] = sbase + u_src(tid + r * 384);
        dst[r] = sbase + u_dst(tid + r * 384);
      }
      asm volatile("bar.sync 0, 512;\n" ::: "memory");
      mbar_wait(bars + (B_WF + 1) * 8);
      if (TSX == 1) TSE(39);
#pragma unroll
      for (int r = 0; r < 3; r++) {
        if (SPLITW && r == 1) mbar_wait(bars + (B_WF + 2) * 8);
#pragma unroll
        for (int k = 0; k < 3; k++) lds128(g[r][k], src[r] + k * 3 * RAWT);
        if (SPLITW && r == 0) u_math16(g[0], dst[0]);
      }
#pragma unroll
      for (int r = SPLITW; r < 3; r++) u_math16(g[r], dst[r]);
      proxy_fence();
      __syncwarp();
      arrive_if(lane == 0 ? bars + B_WF * 8 : 0u);
      TSB(7);
    }
    asm volatile("setmaxnreg.inc.sync.aligned.u32 224;\n");
    float m[4][48];
    const uint32_t vb = sbase + SM_V + wg * UNIT;
    const uint64_t bd0 = w_desc(sbase + SM_W), ad12 = a_desc(vb + 2 * PLANE), ad05 = a_desc(vb + (wg ? 4 * PLANE : 0));

    const uint64_t d34 = wg ? -(2 * PLANE >> 4) : 2 * PLANE >> 4;
    uint64_t ad = ad12;
    uint32_t wf = bars + B_WF * 8, a[4];
    {
      const int t = thread_id();
#pragma unroll
      for (int j = 0; j < 4; j++) a[j] = swz(vb + j * PLANE + ((t & 127) >> 3) * 64, t >> 1) + (t & 1) * 8;
    }
#pragma unroll 1
    for (int sl = 0; sl < 3; sl++) {
      {
        uint32_t d[6][2], d2[6][2];
        const uint32_t a5 = y0 == 216 && ((wg ^ ry) & 1) ? a[0] : a[1], o34 = wg ? 0 : 4 * PLANE;
        mbar_wait(bars + (B_XF + sl * 2 + wg) * 8);
        if (CG == 1 && wg) mbar_wait(bars + B_XR * 8);
        if (CG == 2 && (wg | sl)) mbar_wait(bars + (B_XR + sl * 2 + wg - 1) * 8);
        const uint32_t txf = clock32();
        v_load(d, a, a5, 2048);
        if (CPF) v_load(d2, a, a5, 3072);
        v_store(d, a, 4 * PLANE - o34, o34, 2048);
        if (!CPF) v_load(d2, a, a5, 3072);
        v_store(d2, a, 4 * PLANE - o34, o34, 3072);
        proxy_fence();
        __syncwarp();
        if (elect_one()) arrive_if(bars + (B_XR + sl * 2 + wg) * 8);
        TSB(8 + sl * 3);
#pragma unroll
        for (int j = 0; j < 4; j++) asm volatile("add.u32 %0, %0, %1;\n" : "+r"(a[j]) : "n"(2 * UNIT));
        const uint32_t tw0 = clock32();
        mbar_wait(wf);
        const uint32_t tw1 = clock32();
        mbar_wait(bars + (B_XR + sl * 2 + wg) * 8);
        if (wg && sl >= LOCK) asm volatile("bar.sync 6, 256;\n" ::: "memory");
        if (LOCK0 && !wg && sl) asm volatile("bar.sync 7, 256;\n" ::: "memory");
        if (TSX == 4) { TSE(43 + sl * 4); uint32_t* q = tsp + blockIdx.x * 1024 + wid * 64 + 40 + sl * 4; q[0] = txf - tstart; q[1] = tw0 - tstart; q[2] = tw1 - tstart; }
        TSB(9 + sl * 3);
        if (TSX == 2) TSE(44 + sl);
      }
#pragma unroll
      for (int n = 0; n < 8; n++) {
        const int k = n & 3;
        wgmma_fence();
#pragma unroll
        for (int kj = 0; kj < 3; kj++)
          wgmma_ss(m[k], (k < 2 ? ad : ad + d34) + (k & 1) * (PLANE >> 4) + n / 4 * 2 + kj * 4, bd0 + n * (SLOT >> 4) + kj * 192, (n / 4 | kj) ? 1 : sl);
        wgmma_commit();
        if (n == LOCKN && !wg && sl >= LOCK) asm volatile("bar.arrive 6, 256;\n" ::: "memory");
        if (LOCK0 && n == LOCKN && wg && sl < 2) asm volatile("bar.arrive 7, 256;\n" ::: "memory");
        if (n < 7) {
          if (sl) mbar_wait(wf + (n + 1) * 8);
          wgmma_wait<1>();
          if (warp == 0 && n) asm volatile("bar.arrive %0, 96;\n" ::"r"(7 + n) : "memory");
          if ((BUB >> n) & 1) wgmma_wait<0>();
        }
      }
      if (!LATE4 && sl == 2 && wg) asm volatile("bar.arrive 4, 256;\n" ::: "memory");
      wgmma_wait<1>();
      if (LATE4 && sl == 2 && wg) asm volatile("bar.arrive 4, 256;\n" ::: "memory");
      if (warp == 0) asm volatile("bar.arrive 14, 96;\n" ::: "memory");
      wgmma_wait<0>();
      if (warp == 0) asm volatile("bar.arrive 15, 96;\n" ::: "memory");
      TSB(10 + sl * 3);
      if (TSX == 4) TSE(56 + sl);
      ad += 2 * UNIT >> 4;
      wf += 64;

    }
    const int lane = thread_id() & 31;
    const uint32_t stg = sbase + SM_X + 2 * UNIT + wg * 21504 + warp * 1024 + (lane & 15) * 64 + ((((lane >> 4) ^ (lane >> 1)) & 3) << 4);
    const uint32_t stb = lane == 0 ? bars + (B_ST + wg * 4) * 8 : 0u;
    auto publish = [&](int k) {
      proxy_fence();
      __syncwarp();
      arrive_if(stb ? stb + k * 8 : 0u);
    };
#pragma unroll
    for (int k = 0; k < 4; k++) acc_fence(m[k]);
    float dep = 0.f;
#pragma unroll
    for (int i0 = 0; i0 < 48; i0 += TGRP) {
#pragma unroll
      for (int e = 0; e < TX; e++) asm volatile("add.f32 %0, %0, %0;\n" : "+f"(dep));
      const float k0 = __uint_as_float((__float_as_uint(dep) & never) | 0xbf088889u);
      const float k1 = __uint_as_float((__float_as_uint(dep) & never) | 0xbf800000u);
#pragma unroll
      for (int i = i0; i < i0 + TGRP; i++) {
        m[0][i] *= k0;
        m[3][i] = fmaf(k1, m[3][i], m[2][i]);
        m[1][i] = fmaf(-8.0f / 15.0f, m[1][i], m[0][i]);
        m[2][i] = fmaf(-0.5f, m[3][i], m[2][i]);
        m[0][i] = fmaf(-0.5f, m[1][i], m[0][i]);
        m[1][i] = fmaf(4.0f / 15.0f, m[2][i], m[1][i]);
        m[0][i] = fmaf(4.0f / 15.0f, m[3][i], m[0][i]);
        m[2][i] = fmaf(0.25f, m[1][i], m[2][i]);
        m[3][i] = fmaf(0.25f, m[0][i], m[3][i]);
        dep = m[TDEP][i];
        if ((i & 7) == 7) {
          stage16<4096>(m[2], i >> 3, stg);
          stage16<4096>(m[0], i >> 3, stg + 2 * UNIT);
        }
      }
    }
    publish(0);
    TSB(20);
    asm volatile("bar.sync %0, 256;\n" ::"r"(4 + wg) : "memory");
    TSB(21);
    const uint64_t bdx = w_desc(sbase + SM_X);
    const uint32_t s05 = vb + (wg ? 4 * PLANE : 0) + warp * 1024 + (lane & 15) * 64;
#pragma unroll
    for (int j = 0; j < 12; j++) {
      float* acc = j < 6 ? m[1] : m[3];
      const int c = j % 6;
      const uint64_t ad = ad05 + (c >> 1) * (2 * UNIT >> 4) + (c & 1) * 2 + (j < 6 ? 0 : PLANE >> 4);
      const uint64_t bd = j < 3 ? bdx + j * (SLOT >> 4) : j == 3 ? bdx + ((2 * UNIT + 12288) >> 4) : bd0 + (j - 4) * (SLOT >> 4);
      if (j != 1 && j != 2) mbar_wait(bars + (B_WF + 24 + j) * 8);
      wgmma_fence();
#pragma unroll
      for (int kj = 0; kj < 3; kj++) wgmma_ss(acc, ad + kj * 4, bd + kj * 192);
      wgmma_commit();
      if (j == 3 || j == 5 || j == 7 || j == 9 || j == 11) TSB(22 + j);
      if (PW >= 0 && j < 11) wgmma_wait<PW < 0 ? 0 : PW>();
      if (j == HAND && !wg) asm volatile("bar.arrive 5, 256;\n" ::: "memory");
      if (Y0M == 0) {
        if (j == 7) {
          wgmma_wait<2>();
          acc_fence(m[1]);
        }
        if (j >= 7 && j <= 9) {
#pragma unroll
          for (int jp = j * 2 - 14; jp < j * 2 - 12; jp++) stage16<2 * UNIT>(m[1], jp, swz(s05, lane >> 4));
        }
      } else if (j == 5 + Y0M) {
        wgmma_wait<Y0M>();
        acc_fence(m[1]);
#pragma unroll
        for (int jp = 0; jp < 6; jp++) stage16<2 * UNIT>(m[1], jp, swz(s05, lane >> 4));
      }
      if (j == PUB1) publish(1);
    }
    wgmma_wait<0>();
    acc_fence(m[3]);
    const uint32_t tend = clock32();
    if (HAND == 13 && !wg) asm volatile("bar.arrive 5, 256;\n" ::: "memory");
#pragma unroll
    for (int jp = 0; jp < 6; jp++) stage16<2 * UNIT>(m[3], jp, swz(s05 + PLANE, lane >> 4));
    if (HAND == 12 && !wg) asm volatile("bar.arrive 5, 256;\n" ::: "memory");
    publish(2);
    }
    int rounds = 1;
    const int tid = thread_id(), lane = tid & 31;
    if (cta < 48 || cta >= NI) {
      mbar_wait(bars + B_OK * 8);
      rounds = lds32(bars + O_VER) != FAILED ? 0 : cta < 48 ? 2 : 4;
      rounds = __shfl_sync(0xffffffffu, rounds, 0);
    }
    if (rounds) {
      const bool lead = warp == 0 && elect_one();
      if (rounds > 1) {
        if (tid == 0) {
#pragma unroll
          for (int i = 0; i < 15; i++) mbar_init(bars + (B_G + i) * 8, 1);
          asm volatile("fence.mbarrier_init.release.cluster;\n" ::: "memory");
        }
        proxy_fence();
        asm volatile("bar.sync 3, 256;\n" ::: "memory");
      }
      const uint32_t win = sbase + SM_GX + wg * 3 * GSLICE, gxb = bars + (B_G + 9 + wg * 3) * 8;
      const uint64_t bd0 = w_desc(sbase);
      float acc[48];
#pragma unroll 1
      for (int r = 0; r < rounds; r++) {
        int ty, tx;
        if (cta >= NI) { ty = y0; tx = x0 + r * 16 + wg * 8; }
        else if (cta < 48) { ty = band ? g0 : r * 16 + wg * 8; tx = band ? r * 16 + wg * 8 : g0; }
        else { ty = (cta & 1) * 8 + wg * 16; tx = (cta & 2) * 4 + ((cta >> 2 ^ wg) & 1) * 16; }
        if (lead && rounds > 1) {
#pragma unroll 1
          for (int sl = 0; sl < 3; sl++) {
            mbar_expect_tx(gxb + sl * 8, GSLICE);
            tma_load_3d(win + sl * GSLICE, &tm.gx, gxb + sl * 8, sl * 32, tx - 2, ty - 2);
            if (r == 0) {
#pragma unroll 1
              for (int ki = 0; ki < 3; ki++) {
                if (!wg) mbar_expect_tx(bars + (B_G + sl * 3 + ki) * 8, 2 * SLOT);
                tma_load_5d(sbase + ((sl * 3 + ki) * 2 + wg) * SLOT, &tm.bw[1], bars + (B_G + sl * 3 + ki) * 8, sl * 32 + wg * 16, 0, ki);
              }
            }
          }
        }
        const int ph = ty + warp * 2 + ((lane >> 3) & 1), pw = tx + (lane & 7);
        const uint32_t* op = offs + (ph * IW + pw) * 9;
        const uint32_t base = pack2((float)ph, (float)pw);
        uint32_t ent[9], cf[36], need = 0, out = 0;
#pragma unroll
        for (int m = 0; m < 9; m++) ent[m] = __ldg(op + m);
#pragma unroll
        for (int m = 0; m < 9; m++) {
          const uint32_t pos = clip2(hadd2(hadd2(base, tap_delta(m / 3, m % 3)), ent[m])), fr = frac2(pos);
          const uint32_t iy = (int)bf16lo(pos) - (ty - 2), ix = (int)bf16hi(pos) - (tx - 2);
          out |= max(iy, ix) > 10;
          need |= ((fr >> 16 ? 1u : 0u) | (fr & 0xffffu ? 2u : 0u) | (fr >> 16 && (fr & 0xffffu) ? 4u : 0u)) << (m * 3);
          const uint32_t pp = (iy * 12 + ix) * 0x10001u + 0x10000u;
          ent[m] = (pp * 64 + ((pp << 3) & 0x300030u)) ^ ((lane >> 4) * 0x100010u);
          coefs(__shfl_sync(0xffffffffu, fr, lane >> 2), cf[m * 4], cf[m * 4 + 1]);
          coefs(__shfl_sync(0xffffffffu, fr, (lane >> 2) + 8), cf[m * 4 + 2], cf[m * 4 + 3]);
        }
        need = __reduce_or_sync(0xffffffffu, need);
        asm volatile("{\n.reg .pred p;\nsetp.ne.u32 p, %0, 0;\nbarrier.red.popc.u32 %0, %1, 128, p;\n}\n" : "+r"(out) : "r"(1 + wg) : "memory");
        out = __shfl_sync(0xffffffffu, out, 0);
        TSE(0);
        if (!out) {
          uint32_t C[2][4][8], A[2][8];
#pragma unroll
          for (int i = 0; i < 64; i++) C[0][0][i] = 0;
          auto fetch = [&](uint32_t (*c)[8], int m, uint32_t slice) {
            const uint32_t a0 = (ent[m] & 0xffffu) + slice, a1 = (ent[m] >> 16) + slice;
#pragma unroll
            for (int h = 0; h < 2; h++) {
              ldsm4(c[0] + h * 4, a0 ^ (h * 32));
              ldsm4_if(c[1] + h * 4, a1 ^ (h * 32), need & (1 << (m * 3)));
              ldsm4_if(c[2] + h * 4, (a0 ^ (h * 32) ^ 32) + 768, need & (2 << (m * 3)));
              ldsm4_if(c[3] + h * 4, (a1 ^ (h * 32) ^ 32) + 768, need & (4 << (m * 3)));
            }
          };
#pragma unroll 1
          for (int sl = 0; sl < 3; sl++) {
            const uint32_t slice = win + sl * GSLICE;
            const uint64_t bd = bd0 + sl * (6 * SLOT >> 4);
            mbar_wait(gxb + sl * 8, r & 1);
            fetch(C[0], 0, slice);
#pragma unroll
            for (int m = 0; m < 9; m++) {
              if (m < 8) fetch(C[~m & 1], m + 1, slice);
              if (m % 3 == 0) mbar_wait(bars + (B_G + sl * 3 + m / 3) * 8);
              if (m >= 2) wgmma_wait<1>();
#pragma unroll
              for (int i = 0; i < 8; i++)
                A[m & 1][i] = blend(cf[m * 4 + (i & 1) * 2], cf[m * 4 + (i & 1) * 2 + 1], C[m & 1][0][i], C[m & 1][1][i], C[m & 1][2][i], C[m & 1][3][i]);
              wgmma_fence();
              wgmma_rs(acc, A[m & 1], bd + m / 3 * (2 * SLOT >> 4) + m % 3 * 192, m ? 1 : sl);
              wgmma_rs(acc, A[m & 1] + 4, bd + (m / 3 * 2 + 1) * (SLOT >> 4) + m % 3 * 192);
              wgmma_commit();
            }
            wgmma_wait<0>();
          }
        } else {
#pragma unroll 1
          for (int i = 0; i < 12; i++) mbar_wait(i < 9 ? bars + (B_G + i) * 8 : gxb + (i - 9) * 8, i < 9 ? 0 : r & 1);
          const uint32_t scratch = win + warp * 3072 + lane * 16;
#pragma unroll 1
          for (int m = 0; m < 9; m++) {
            const int ki = (m * 11) >> 5;
            const uint32_t pos = clip2(hadd2(pack2((float)(ph + ki - 1), (float)(pw + m - ki * 3 - 1)), __ldg(op + m)));
            const int gy = (int)bf16lo(pos), gx = (int)bf16hi(pos), sx = gx < IW - 1 ? 12 : 0, sy = gy < IH - 1 ? IW * 12 : 0;
            const uint4* pc = x + (gy * IW + gx) * 12 + (lane >> 4);
            uint32_t q0, q1, V[6][4][4], A[6][4];
            coefs(frac2(pos), q0, q1);
#pragma unroll
            for (int k = 0; k < 6; k++)
#pragma unroll
              for (int c = 0; c < 4; c++) ldg128(V[k][c], pc + k * 2 + (c & 1) * sx + (c >> 1) * sy);
#pragma unroll
            for (int k = 0; k < 6; k++) {
#pragma unroll
              for (int i = 0; i < 4; i++) V[k][0][i] = blend(q0, q1, V[k][0][i], V[k][1][i], V[k][2][i], V[k][3][i]);
              sts128(scratch + k * 512, V[k][0]);
            }
            __syncwarp();
#pragma unroll
            for (int k = 0; k < 6; k++) ldsm4(A[k], scratch + k * 512);
            wgmma_fence();
#pragma unroll
            for (int k = 0; k < 6; k++) wgmma_rs(acc, A[k], bd0 + ((k >> 1) * 6 + ki * 2 + (k & 1)) * (SLOT >> 4) + (m - ki * 3) * 192, k ? 1 : m);
            wgmma_commit();
            wgmma_wait<0>();
          }
        }
        acc_fence(acc);
        TSE(1);
        asm volatile("bar.sync %0, 128;\n" ::"r"(1 + wg) : "memory");
#pragma unroll
        for (int jp = 0; jp < 6; jp++) stage16<4096>(acc, jp, win + warp * 1024 + (lane & 15) * 64 + ((((lane >> 4) ^ (lane >> 1)) & 3) << 4));
        proxy_fence();
        asm volatile("bar.sync %0, 128;\n" ::"r"(1 + wg) : "memory");
        if (lead) {
          tma_store(&tm.gout, win, tx, ty);
          asm volatile("cp.async.bulk.commit_group;\ncp.async.bulk.wait_group.read 0;\n" ::: "memory");
          TSE(2);
        }
      }
    }
  } else if (wid < 12) {
    asm volatile("setmaxnreg.dec.sync.aligned.u32 %0;\n" ::"n"(R2));
    const int tid = thread_id(), lane = tid & 31;

    const bool one = elect_one();
    if (one && cta < NI) {
#pragma unroll
      for (int i = 0; i < 4; i++) mbar_init(bars + (B_G + (wid - 8) * 4 + i) * 8, 1);
      asm volatile("fence.mbarrier_init.release.cluster;\n" ::: "memory");
    }
    if (one && cta >= NI) {
#pragma unroll
      for (int i = 0; i < 7; i++) mbar_init(bars + (B_WF + 8 + (wid - 8) * 7 + i) * 8, 1);
      if (wid == 8) mbar_init(bars + B_WF * 8, 12);
      mbar_init(bars + (B_UR + wid - 8) * 8, 1);
      asm volatile("fence.mbarrier_init.release.cluster;\n" ::: "memory");
    }
    asm volatile("bar.arrive 3, 256;\n" ::: "memory");
    asm volatile("bar.sync 0, 512;\n" ::: "memory");
    if (cta >= NI) {
      mbar_wait(bars + (B_WF + 1) * 8);
#pragma unroll 1
      for (int t = tid; t < 1152; t += 384) {
        uint32_t g[3][4];
        const uint32_t src = sbase + u_src(t);
        if (SPLITW && t >= 384) mbar_wait(bars + (B_WF + 2) * 8);
#pragma unroll
        for (int k = 0; k < 3; k++) lds128(g[k], src + k * 3 * RAWT);
        u_math16(g, sbase + u_dst(t));
      }
      proxy_fence();
      __syncwarp();
      arrive_if(one ? bars + B_WF * 8 : 0u);
      uint32_t a[4], d[2][6][2];
#pragma unroll
      for (int j = 0; j < 4; j++) a[j] = swz(sbase + SM_V + j * PLANE + ((tid & 127) >> 3) * 64, lane >> 1) + (lane & 1) * 8;
      const bool bot = y0 == 216;
      uint32_t tsv = 0;
      uint32_t off = 0;
#pragma unroll 1
      for (int u = 0; u < 6; u++) {
        const uint32_t a5 = bot && ((u ^ ry) & 1) ? a[0] : a[1], o34 = u & 1 ? 0 : 4 * PLANE;
        mbar_wait(bars + (B_XF + u) * 8);
        if (VGATE == 1 && u >= 1) mbar_wait(bars + (B_XR + u - 1) * 8);
        if (VGATE == 2 && u == 1) mbar_wait(bars + B_XR * 8);
        if (SPF) v_load(d[0], a, a5, off);
#pragma unroll
        for (int i = 0; i < 4 - VC; i++) {
          if (SPF) {
            if (i < 3 - VC) v_load(d[~i & 1], a, a5, off + (i + 1) * 1024);
            v_store(d[i & 1], a, 4 * PLANE - o34, o34, off + i * 1024);
          } else {
            v_load(d[0], a, a5, off + i * 1024);
            v_store(d[0], a, 4 * PLANE - o34, o34, off + i * 1024);
          }
        }
        if ((u & 3) == (wid & 3) && lane < 16) {
          const uint32_t h = off + 4096 - (wid & 2) * 256;
          v_load(d[1], a, a5, x0 == 160 && lane >= 8 ? h - 64 : h);
          v_store(d[1], a, 4 * PLANE - o34, o34, h);
        }
        proxy_fence();
        __syncwarp();
        arrive_if(one ? bars + (B_XR + u) * 8 : 0u);
        if (TSBON && lane == u) tsv = clock32() - tstart;
        off += UNIT + ((u ^ wid) & 1 ? -256 : 256);
      }
    }
  } else {
    asm volatile("setmaxnreg.dec.sync.aligned.u32 %0;\n" ::"n"(64 - R2));
    const int tid = thread_id(), lane = tid & 31;
    const bool one = elect_one();
    if (wid != 12) {
      if (one) {
        if (cta >= NI) {
          if (wid == 13) {
#pragma unroll
            for (int i = 0; i < 6; i++) mbar_init(bars + (B_XR + i) * 8, 8);
          } else if (wid == 15) {
#pragma unroll
            for (int i = 1; i < 6; i++) mbar_init(bars + (B_XF + i) * 8, 1);
          }
        } else {
#pragma unroll
          for (int i = 0; i < 3; i++) mbar_init(bars + (B_WF + 1 + (wid - 13) * 3 + i) * 8, 1);
          mbar_init(bars + (wid == 13 ? B_WE : B_UR + wid - 14) * 8, wid == 13 ? 8 : 1);
          if (wid < 15) mbar_init(bars + (B_XF + wid - 12) * 8, 1);
        }
        if (wid == 14) {
#pragma unroll
          for (int i = 0; i < 8; i++) mbar_init(bars + (B_ST + i) * 8, 4);
#pragma unroll
          for (int i = B_OF; i <= B_OK; i++) mbar_init(bars + i * 8, i != B_OS ? 1 : cta < NI ? 8 : 2);
          sts64(bars + O_CNT, 0, 0);
          sts64(bars + O_CNT + 8, 0, 0);
        }
        asm volatile("fence.mbarrier_init.release.cluster;\n" ::: "memory");
      }
      asm volatile("bar.arrive 3, 256;\n" ::: "memory");
      asm volatile("bar.sync 0, 512;\n" ::: "memory");
      if (cta >= 48 && cta < NI) {
        if (wid == 15 && one) asm volatile("red.relaxed.gpu.global.add.u32 [%0], 1;\n" ::"l"(scr->ready + 6) : "memory");
      } else {
        uint32_t epoch = 0;
        if (cta >= NI && wid < 15) {
          const uint32_t lim = (pack2((float)max(y0, 34) - 1.5f, (float)max(x0, 34) - 1.5f) & 0x7f807f80u) - 0x04000400u;
          uint32_t big = 0;
          mbar_wait(bars + B_OF * 8);
          TSE(6);
#pragma unroll 1
          for (int i0 = 0; i0 < 18; i0 += SCANB) {
            uint32_t v[SCANB][4];
#pragma unroll
            for (int i = 0; i < SCANB; i++) lds128(v[i], sbase + SM_OFF + (tid - 416) * 16 + (i0 + i) * 1024);
            __nv_bfloat162 mx = as_bf2(0u), mn = as_bf2(0u);
#pragma unroll
            for (int i = 0; i < SCANB * 2; i++) {
              mx = __hmax2_nan(__hmax2_nan(mx, as_bf2(v[i >> 1][(i & 1) * 2])), as_bf2(v[i >> 1][(i & 1) * 2 + 1]));
              mn = __hmin2_nan(__hmin2_nan(mn, as_bf2(v[i >> 1][(i & 1) * 2])), as_bf2(v[i >> 1][(i & 1) * 2 + 1]));
            }
            big = (big << SCANB) | (__hblt2(__hmax2_nan(mx, __hneg2(mn)), as_bf2(lim)) ? 0u : (1u << SCANB) - 1);
          }
          if (big) {
            mbar_wait(bars + B_EP * 8);
            epoch = lds32(bars + O_EPO);
          }
#pragma unroll 1
          for (int k = 0; big; k++) {
            const uint32_t wi = (tid - 416 + (18 - __ffs(big)) * 64) * 4 + (k & 3), id = (wi * 7282) >> 16, tap = wi - id * 9;
            const int ki = (tap * 11) >> 5, h = y0 + (id >> 6), w = x0 + (id & 63);
            const uint32_t gp = pack2((float)(h + ki - 1), (float)(w + (int)tap - ki * 3 - 1)), pos = clip2(hadd2(gp, lds32(sbase + SM_OFF + wi * 4)));
            if (pos != hmin2(gp, 0x435f435fu) && h >= 34 && w >= 34) {
              const uint32_t i = count_up(bars + O_CNT);
              if (i >= MAXEX) break;
              sts32(bars + O_LST + i * 4, id | (request(scr, min(atomicAdd(scr->ready + 8 + ((epoch >> 7) & 1), 1u) + EARLY, QUEUE), pos, h, w, tap) << 16));
            }
            if ((k & 3) == 3) big &= big - 1;
          }
          __syncwarp();
          arrive_if(one ? bars + B_OS * 8 : 0u);
        }
        if (wid == 13) {
          uint32_t m[2] = {}, cnt = 0;
          mbar_wait(bars + B_OS * 8);
          if (cta >= NI) {
            mbar_wait(bars + (B_WF + X5W) * 8);
            if (one) {
              mbar_expect_tx(bars + (B_XF + 5) * 8, UNIT);
              tma_load_3d(sbase + SM_V + 5 * UNIT, &tm.x, bars + (B_XF + 5) * 8, 64, x0 - 1, y0 + (~ry & 1) * 4 - 1);
            }
          }
          TSE(7);
          mbar_wait(bars + B_EP * 8);
          epoch = lds32(bars + O_EPO);
          if (cta >= NI ? x0 == 32 || y0 == 32 : g0 == 32) {
#pragma unroll 1
            for (uint32_t spin = 0;; spin++) {
              ld_pair(m, scr->mail[cta] + min(lane, MAXEX));
              const uint32_t have = __ballot_sync(0xffffffffu, m[1] == epoch);
              cnt = __reduce_max_sync(0xffffffffu, lane == MAXEX ? m[0] : 0u);
              if ((have >> MAXEX) && (cnt > MAXEX || !(~have & ((1u << cnt) - 1)))) break;
              if (spin > (1u << 22)) __trap();
            }
          }
          if (one) asm volatile("red.relaxed.gpu.global.add.u32 [%0], 1;\n" ::"l"(scr->ready + 6) : "memory");
          const uint32_t own = lds32(bars + O_CNT);
          if (own && lane >= cnt) m[0] = lds32(bars + O_LST + ((lane - cnt) & 15) * 4);
          cnt += own;
          if (cnt > MAXEX || __any_sync(0xffffffffu, lane < cnt && m[0] >> 16 == QUEUE)) cnt = FAILED;
          sts32(bars + O_LST + lane * 4, lane < cnt ? m[0] & 511 : 512);
#pragma unroll 1
          for (uint32_t got = 0; got < cnt && cnt != FAILED; got += 4) {
            const uint32_t i = min(got + (lane >> 3), cnt - 1);
            const uint2* r = scr->res[__shfl_sync(0xffffffffu, m[0], i) >> 16] + (lane & 7);
            uint32_t v[12];
#pragma unroll 1
            for (uint32_t spin = 0;; spin++) {
              uint32_t miss = 0;
#pragma unroll
              for (int k = 0; k < 6; k++) ld_pair(v + k * 2, r + k * 8);
#pragma unroll
              for (int k = 0; k < 6; k++) miss |= v[k * 2 + 1] ^ epoch;
              if (__all_sync(0xffffffffu, !miss)) break;
              if (spin > (1u << 22)) __trap();
            }
#pragma unroll
            for (int k = 0; k < 6; k++) sts32(bars + O_COR + i * 192 + (lane & 7) * 4 + k * 32, v[k * 2]);
          }
          if (one) sts32(bars + O_VER, cnt);
          __syncwarp();
          arrive_if(one ? bars + B_OK * 8 : 0u);
          TSE(0);
        } else {
          if (wid == 15) {
            auto poll = [&]() {
              uint32_t v;
              asm volatile("ld.relaxed.gpu.global.u32 %0, [%1];\n" : "=r"(v) : "l"(scr->ready + min(lane, 6)) : "memory");
              return v;
            };
            const uint32_t epoch = (__reduce_max_sync(0xffffffffu, lane == 6 ? poll() : 0u) & ~127u) + 128;
            if (one) sts32(bars + O_EPO, epoch);
            arrive_if(one ? bars + B_EP * 8 : 0u);
            if (cta >= NI) {
              uint32_t v[PFLY], seen = 0;
              wait_until(tstart, POLLT);
#pragma unroll
              for (int i = 0; i < PFLY - 1; i++) {
                v[i] = poll();
                __nanosleep(PGAP);
              }
#pragma unroll 1
              for (uint32_t spin = 0; seen != 7; spin++) {
#pragma unroll
                for (int i = 0; i < PFLY; i++) {
                  v[(i + PFLY - 1) % PFLY] = poll();
                  const uint32_t now = __ballot_sync(0xffffffffu, v[i] == epoch) & ~seen & 7;
                  if (now) {
                    asm volatile("fence.proxy.async.global;\n" ::: "memory");
                    arrive_if((now >> lane) & 1 ? bars + (B_UR + lane) * 8 : 0u);
                    seen |= now;
                    if (TSX == 4) TSE(8 + __popc(seen));
                  }
                }
                if (spin > (1u << 20)) __trap();
              }
            }
            TSE(4);
          }
          const int t = wid & 1;
          mbar_wait(bars + B_OK * 8);
          const uint32_t cnt = lds32(bars + O_VER);
          if (cnt != FAILED) {
            const uint32_t id = lds32(bars + O_LST + lane * 4);
            mbar_wait(bars + (B_ST + t * 4) * 8);
            if (cta < NI) {
              patch(id, t * 128, 128, sbase + t * 3 * SLOT, 8192, bars, lane);
              if (one) tma_store(&tm.bout[band], sbase + t * 3 * SLOT, g0, t * 16);
            } else {
              const int r0 = ((t ^ ry) & 1) * 4;
#pragma unroll 1
              for (int r = 0; r < 4; r++) {
                const uint32_t base = r < 2 ? sbase + SM_X + (2 + r * 2) * UNIT + t * 21504 : sbase + SM_V + t * (UNIT + 4 * PLANE) + (r - 2) * PLANE;
                const uint32_t pitch = r < 2 ? 4096 : 2 * UNIT;
                const int row = r0 + ((2 - r) & 3);
                if (r >= 2) mbar_wait(bars + (B_ST + t * 4 + r - 1) * 8);
                patch(id, row * 64, 64, base, pitch, bars, lane);
#pragma unroll
                for (int k = 0; k < 3; k++)
                  if (one) tma_store3(&tm.out, base + k * pitch, k * 32, x0, y0 + row);
              }
            }
            if (one) asm volatile("cp.async.bulk.commit_group;\ncp.async.bulk.wait_group.read 0;\n" ::: "memory");
            TSE(2);
          }
        }
      }
    } else if (cta < NI) {
        auto load_x = [&](int s) {
          mbar_expect_tx(bars + (B_XF + s) * 8, YSLICE);
          tma_load_3d(sbase + SM_YX + s * YSLICE, &tm.bx[band], bars + (B_XF + s) * 8, s * 32, g0 - 1, -2);
        };
        auto load_w = [&](int p) {
          const int s = (p * 11) >> 5, b = p - s * 3;
          mbar_expect_tx(bars + (B_WF + p) * 8, 2 * SLOT);
#pragma unroll
          for (int h = 0; h < 2; h++)
            tma_load_5d(sbase + (p * 2 + h) * SLOT, &tm.bw[band], bars + (B_WF + p) * 8, s * 32 + h * 16, band ? 0 : b, band ? b : 0);
        };
        asm volatile("bar.sync 3, 256;\n" ::: "memory");
        if (one && cta >= 48) {
#pragma unroll 1
          for (int sl = 0; sl < 3; sl++) {
            wait_until(tstart, sl * GDT);
#pragma unroll
            for (int wg = 0; wg < 2; wg++) {
              mbar_expect_tx(bars + (B_G + 9 + wg * 3 + sl) * 8, GSLICE);
              tma_load_3d(sbase + SM_GX + (wg * 3 + sl) * GSLICE, &tm.gx, bars + (B_G + 9 + wg * 3 + sl) * 8, sl * 32,
                          (cta & 2) * 4 + ((cta >> 2 ^ wg) & 1) * 16 - 2, (cta & 1) * 8 + wg * 16 - 2);
            }
#pragma unroll 1
            for (int i = 0; i < 6; i++) {
              if (!(i & 1)) mbar_expect_tx(bars + (B_G + sl * 3 + (i >> 1)) * 8, 2 * SLOT);
              tma_load_5d(sbase + (sl * 6 + i) * SLOT, &tm.bw[1], bars + (B_G + sl * 3 + (i >> 1)) * 8, sl * 32 + (i & 1) * 16, 0, i >> 1);
            }
          }
        }
        if (one && cta < 48) {
          arrive_if(bars + (B_WF + 9) * 8);
#pragma unroll 1
          for (int p = 1; p < 9; p++) {
            wait_until(tstart, YWT + (p - 1) * YWDT);
            if (p == YP1) load_x(1);
            if (p == YP2) load_x(2);
            if (p == 8) mbar_wait(bars + B_WE * 8);
            load_w(p);
            if (p >= PFP && p < PFP + 3 / PFK) {
#pragma unroll
              for (int k = 0; k < PFK; k++) {
                const int i = ((p - PFP) * PFK + k) * 48 + cta, sec = i >= 72, j = i - sec * 72, jy = j / 3;
                asm volatile("cp.async.bulk.prefetch.tensor.3d.L2.global [%0, {%1, %2, %3}];\n" ::"l"(reinterpret_cast<uint64_t>(&tm.xp)), "r"(64),
                             "r"(32 + (j - jy * 3) * 64), "r"(32 + jy * 8 + ((jy ^ sec) & 1) * 4) : "memory");
              }
            }
          }
        }
    } else {
        auto load_x = [&](int u) {
          mbar_expect_tx(bars + (B_XF + u) * 8, UNIT);
          tma_load_3d(sbase + SM_V + u * UNIT, &tm.x, bars + (B_XF + u) * 8, (u >> 1) * 32, x0 - 1, y0 + ((u ^ ry) & 1) * 4 - 1);
        };
        asm volatile("bar.sync 3, 256;\n" ::: "memory");
        if (lane < 28) mbar_expect_tx(bars + (B_WF + 8 + lane) * 8, lane == 16 ? 3 * SLOT : lane == 17 || lane == 18 ? 0 : SLOT);
        if (smem_u32(smem) != sbase) __trap();
#pragma unroll 1
        for (int xu = 1; xu <= XN; xu++) {
          wait_until(tstart, XT1 + (xu - 1) * XDT);
          if (xu == 3) mbar_wait(bars + B_WF * 8);
          if (one) load_x(xu);
          if (xu == OFFAT && one) {
            mbar_expect_tx(bars + B_OF * 8, 2 * SLOT);
            tma_load_3d(sbase + SM_OFF, &tm.off, bars + B_OF * 8, 0, x0 * 9 / 32, y0);
          }
        }
        const uint4* src = scr->u;
        uint32_t fb = bars + (B_WF + 8) * 8;
#pragma unroll 1
        for (int q = 0; q < 6; q++) {
          mbar_wait(bars + (B_UR + (q >> 1)) * 8);
          if (q == 4) {
            if (one) bulk_load<3 * SLOT>(sbase + SM_X, src, fb);
            if (one) bulk_load<SLOT>(sbase + SM_X + 2 * UNIT + 12288, src + 3 * 576, fb + 24);
            src += 4 * 576;
            fb += 32;
          }
          const uint32_t dst = sbase + SM_W + (q & 1) * 4 * SLOT, id = 8 + (q & 1) * 4;
#pragma unroll
          for (int k = 0; k < 4; k++) {
            asm volatile("bar.sync %0, 96;\n" ::"r"(id + k) : "memory");
            if (one) bulk_load<SLOT>(dst + k * SLOT, src + k * 576, fb + k * 8);
          }
          if (q == 1 && one) {
            if (XN < 4) load_x(4);
          }
          src += 4 * 576;
          fb += 32;
        }
    }
  }
}

typedef CUresult (*EncodeTiledFn)(CUtensorMap*, CUtensorMapDataType, cuuint32_t, void*, const cuuint64_t*,
                                  const cuuint64_t*, const cuuint32_t*, const cuuint32_t*, CUtensorMapInterleave,
                                  CUtensorMapSwizzle, CUtensorMapL2promotion, CUtensorMapFloatOOBfill);

}

extern "C" void kernel_launch(void* const* d_in, const int* in_sizes, int n_in, void* d_out, int out_size) {
  static EncodeTiledFn encode = nullptr;
  static Scratch* scratch = nullptr;
  if (!encode) {
    void* fn = nullptr;
    cudaDriverEntryPointQueryResult qres;
    cudaGetDriverEntryPoint("cuTensorMapEncodeTiled", &fn, cudaEnableDefault, &qres);
    encode = (EncodeTiledFn)fn;
    cudaGetSymbolAddress((void**)&scratch, g_scratch);
    cudaFuncSetAttribute(dcn_kernel, cudaFuncAttributeMaxDynamicSharedMemorySize, SMEM_BYTES);
  }
  uint32_t* tsp = nullptr;
  Maps tm;
  auto make = [&](CUtensorMap* m, void* p, int rank, const cuuint64_t* dims, const cuuint64_t* strides, const cuuint32_t* box, bool swizzle) {
    const cuuint32_t es[5] = {1, 1, 1, 1, 1};
    encode(m, CU_TENSOR_MAP_DATA_TYPE_BFLOAT16, rank, p, dims, strides, box, es, CU_TENSOR_MAP_INTERLEAVE_NONE,
           swizzle ? CU_TENSOR_MAP_SWIZZLE_64B : CU_TENSOR_MAP_SWIZZLE_NONE, CU_TENSOR_MAP_L2_PROMOTION_NONE,
           CU_TENSOR_MAP_FLOAT_OOB_FILL_NONE);
  };
  const cuuint64_t PX = IC * 2, ROW = IW * IC * 2, TAP = IC * IC * 2;
  for (int t = 0; t < 2; t++) {
    const cuuint64_t dims[3] = {IC, IW, IH}, odims[4] = {32, IW, IH, 3}, strides[3] = {t ? ROW : PX, t ? PX : ROW, 64};
    const cuuint32_t xb[3] = {32, 66, 6}, ob[3] = {32, 64, 1}, bxb[3] = {32, 10, 36}, bob[4] = {32, 8, 16, 3};
    if (!t) make(&tm.x, d_in[0], 3, dims, strides, xb, true);
    const cuuint32_t xpb[3] = {32, 64, 4};
    if (!t) make(&tm.xp, d_in[0], 3, dims, strides, xpb, true);
    if (!t) make(&tm.out, d_out, 3, dims, strides, ob, true);
    const cuuint32_t gxb[3] = {32, 12, 12}, gob[4] = {32, 8, 8, 3};
    if (!t) make(&tm.gx, d_in[0], 3, dims, strides, gxb, true);
    if (!t) make(&tm.gout, d_out, 4, odims, strides, gob, true);
    make(&tm.bx[t], d_in[0], 3, dims, strides, bxb, true);
    make(&tm.bout[t], d_out, 4, odims, strides, bob, true);
    const cuuint64_t wdims[5] = {32, IC, 3, 3, 3}, wstrides[4] = {PX, 64, TAP, 3 * TAP};
    const cuuint32_t wb[5] = {32, 16, 3, t ? 3u : 1u, t ? 1u : 3u};
    make(&tm.bw[t], d_in[2], 5, wdims, wstrides, wb, true);
  }
  {
    const cuuint64_t dims[3] = {64, 144, 9}, strides[2] = {128, TAP};
    const cuuint32_t box[3] = {64, 48, 9};
    make(&tm.w, d_in[2], 3, dims, strides, box, false);
    const cuuint32_t hbox[3] = {64, 24, 9};
    make(&tm.wh, d_in[2], 3, dims, strides, hbox, false);
    const cuuint64_t cdims[4] = {64, 144, 3, 3}, cstrides[3] = {128, TAP, 3 * TAP};
    const cuuint32_t cbox[4] = {64, 24, 1, 3};
    make(&tm.wc, d_in[2], 4, cdims, cstrides, cbox, false);
    const cuuint64_t odims[3] = {64, 63, IH}, ostrides[2] = {128, IW * 36};
    const cuuint32_t obox[3] = {64, 18, 8};
    make(&tm.off, d_in[1], 3, odims, ostrides, obox, false);
    const cuuint32_t cb[3] = {64, 1, IH};
    make(&tm.col, d_in[1], 3, odims, ostrides, cb, false);
  }
  dcn_kernel<<<GRID, NTHREADS, SMEM_BYTES>>>((const uint4*)d_in[0], (const uint32_t*)d_in[1], (const uint4*)d_in[2], scratch, tsp, 0u, tm);
}
```

```cpp
#include <cuda_runtime.h>
#include <cuda.h>
#include <cuda_bf16.h>
#include <stdint.h>

namespace {

constexpr int IH = 224, IW = 224, IC = 96;
constexpr int GRID = 132, NTHREADS = 512;
constexpr int NI = 60;
constexpr int SLOT = 9216;
constexpr int SMEM_BYTES = 232448;
constexpr int PLANE = 66 * 64, UNIT = 6 * PLANE;
constexpr int SM_V = 256, SM_X = SM_V + 2 * PLANE, SM_W = 36 * PLANE + 512, SM_BAR = SM_W + 8 * SLOT;
constexpr int SM_RAW = SM_V + 3 * UNIT, SM_OFF = SM_V + 6 * UNIT - 2 * SLOT;
constexpr int YSLICE = 36 * 10 * 64, SM_YX = 16 * SLOT, SM_YT = SM_YX + 3 * YSLICE;
constexpr int GSLICE = 144 * 64, SM_GX = 18 * SLOT;
constexpr int B_WF = 0, B_WE = 36, B_XF = 60, B_XR = 66, B_ST = 72, B_UR = 80, B_OF = 84, B_OS = 85, B_EP = 86, B_OK = 87, B_G = 88;
constexpr int O_CNT = 832, O_VER = 848, O_EPO = 852, O_LST = 864, O_COR = 1024;
constexpr int MAXEX = 16, EARLY = 128, QUEUE = 192;
constexpr uint32_t FAILED = 0xffff;
#define PACE XT1 = 1900, XDT = 900, POLLT = 4200, YX0 = 1400, YWT = 2500, YWDT = 1100, GDT = 3500
constexpr uint32_t PACE;

struct Scratch {
  uint4 u[16 * SLOT / 16];
  uint4 w[12 * SLOT / 16];
  uint32_t ready[32];
  uint2 req[QUEUE];
  uint2 res[QUEUE][48];
  uint2 mail[GRID][32];
};
__device__ __align__(128) Scratch g_scratch;

#define TSE(i)

__device__ __forceinline__ float bf16lo(uint32_t v) { return __uint_as_float(v << 16); }
__device__ __forceinline__ float bf16hi(uint32_t v) { return __uint_as_float(v & 0xffff0000u); }
__device__ __forceinline__ uint32_t smem_u32(const void* p) { return (uint32_t)__cvta_generic_to_shared(p); }
__device__ __forceinline__ void mbar_init(uint32_t bar, uint32_t count) {
  asm volatile("mbarrier.init.shared::cta.b64 [%0], %1;\n" ::"r"(bar), "r"(count) : "memory");
}
__device__ __forceinline__ void mbar_expect_tx(uint32_t bar, uint32_t bytes) {
  asm volatile("mbarrier.arrive.expect_tx.shared::cta.b64 _, [%0], %1;\n" ::"r"(bar), "r"(bytes) : "memory");
}
__device__ __forceinline__ void mbar_wait(uint32_t bar, uint32_t parity = 0) {
  uint32_t done;
#pragma unroll 1
  for (uint32_t spin = 0; spin < (1u << 22); spin++) {
    asm volatile(
        "{\n.reg .pred p;\n"
        "mbarrier.try_wait.parity.shared::cta.b64 p, [%1], %2;\n"
        "selp.u32 %0, 1, 0, p;\n}\n"
        : "=r"(done)
        : "r"(bar), "r"(parity)
        : "memory");
    if (done) return;
  }
  __trap();
}
__device__ __forceinline__ uint32_t clock32() {
  uint32_t c;
  asm volatile("mov.u32 %0, %%clock;\n" : "=r"(c)::"memory");
  return c;
}
__device__ __forceinline__ void wait_until(uint32_t t0, uint32_t dt) {
  while (clock32() - t0 < dt) __nanosleep(50);
}
__device__ __forceinline__ void tma_load_3d(uint32_t dst, const CUtensorMap* tm, uint32_t bar, int c0, int c1, int c2) {
  asm volatile(
      "cp.async.bulk.tensor.3d.shared::cluster.global.mbarrier::complete_tx::bytes [%0], [%1, {%3, %4, %5}], [%2];\n" ::"r"(dst),
      "l"(reinterpret_cast<uint64_t>(tm)), "r"(bar), "r"(c0), "r"(c1), "r"(c2)
      : "memory");
}
__device__ __forceinline__ void tma_load_5d(uint32_t dst, const CUtensorMap* tm, uint32_t bar, int c, int kj, int ki) {
  asm volatile(
      "cp.async.bulk.tensor.5d.shared::cluster.global.mbarrier::complete_tx::bytes [%0], [%1, {%3, %4, %3, %5, %6}], [%2];\n" ::"r"(dst),
      "l"(reinterpret_cast<uint64_t>(tm)), "r"(bar), "r"(0), "r"(c), "r"(kj), "r"(ki)
      : "memory");
}
__device__ __forceinline__ void tma_load_4d(uint32_t dst, const CUtensorMap* tm, uint32_t bar, int c1, int c2, int c3) {
  asm volatile(
      "cp.async.bulk.tensor.4d.shared::cluster.global.mbarrier::complete_tx::bytes [%0], [%1, {%3, %4, %5, %6}], [%2];\n" ::"r"(dst),
      "l"(reinterpret_cast<uint64_t>(tm)), "r"(bar), "r"(0), "r"(c1), "r"(c2), "r"(c3)
      : "memory");
}
template <int BYTES>
__device__ __forceinline__ void bulk_load(uint32_t dst, const void* src, uint32_t bar) {
  asm volatile("cp.async.bulk.shared::cluster.global.mbarrier::complete_tx::bytes [%0], [%1], %3, [%2];\n" ::"r"(dst), "l"(src),
               "r"(bar), "n"(BYTES)
               : "memory");
}
__device__ __forceinline__ void tma_store3(const CUtensorMap* tm, uint32_t src, int c0, int c1, int c2) {
  asm volatile("cp.async.bulk.tensor.3d.global.shared::cta.bulk_group [%0, {%2, %3, %4}], [%1];\n" ::"l"(
                   reinterpret_cast<uint64_t>(tm)),
               "r"(src), "r"(c0), "r"(c1), "r"(c2)
               : "memory");
}
__device__ __forceinline__ void tma_store(const CUtensorMap* tm, uint32_t src, int c1, int c2) {
  asm volatile("cp.async.bulk.tensor.4d.global.shared::cta.bulk_group [%0, {%2, %3, %4, %2}], [%1];\n" ::"l"(
                   reinterpret_cast<uint64_t>(tm)),
               "r"(src), "r"(0), "r"(c1), "r"(c2)
               : "memory");
}
__device__ __forceinline__ uint64_t w_desc(uint32_t saddr) {
  return (uint64_t)((saddr & 0x3FFFF) >> 4) | ((uint64_t)(1024 >> 4) << 16) | ((uint64_t)(512 >> 4) << 32) | ((uint64_t)2 << 62);
}
__device__ __forceinline__ uint64_t a_desc(uint32_t saddr) {
  return (uint64_t)((saddr & 0x3FFFF) >> 4) | ((uint64_t)1 << 16) | ((uint64_t)(512 >> 4) << 32) | ((uint64_t)2 << 62);
}
#define ACC_OPERANDS(c, d)                                                                                        \
  c(d[0]), c(d[1]), c(d[2]), c(d[3]), c(d[4]), c(d[5]), c(d[6]), c(d[7]), c(d[8]),      \
      c(d[9]), c(d[10]), c(d[11]), c(d[12]), c(d[13]), c(d[14]), c(d[15]), c(d[16]),       \
      c(d[17]), c(d[18]), c(d[19]), c(d[20]), c(d[21]), c(d[22]), c(d[23]), c(d[24]),      \
      c(d[25]), c(d[26]), c(d[27]), c(d[28]), c(d[29]), c(d[30]), c(d[31]), c(d[32]),      \
      c(d[33]), c(d[34]), c(d[35]), c(d[36]), c(d[37]), c(d[38]), c(d[39]), c(d[40]),      \
      c(d[41]), c(d[42]), c(d[43]), c(d[44]), c(d[45]), c(d[46]), c(d[47])
#define ACC_LIST                                                                   \
  "{%0, %1, %2, %3, %4, %5, %6, %7, %8, %9, %10, %11, %12, %13, %14, %15, "        \
  "%16, %17, %18, %19, %20, %21, %22, %23, %24, %25, %26, %27, %28, %29, %30, %31, " \
  "%32, %33, %34, %35, %36, %37, %38, %39, %40, %41, %42, %43, %44, %45, %46, %47}, "
__device__ __forceinline__ void wgmma_ss(float* d, uint64_t adesc, uint64_t bdesc, int accumulate = 1) {
  asm volatile(
      "{\n.reg .pred p;\nsetp.ne.b32 p, %50, 0;\n"
      "wgmma.mma_async.sync.aligned.m64n96k16.f32.bf16.bf16 " ACC_LIST "%48, %49, p, 1, 1, 0, 1;\n}\n"
      : ACC_OPERANDS("+f", d)
      : "l"(adesc), "l"(bdesc), "r"(accumulate));
}
__device__ __forceinline__ void wgmma_fence() { asm volatile("wgmma.fence.sync.aligned;\n" ::: "memory"); }
__device__ __forceinline__ void wgmma_commit() { asm volatile("wgmma.commit_group.sync.aligned;\n" ::: "memory"); }
template <int N>
__device__ __forceinline__ void wgmma_wait() { asm volatile("wgmma.wait_group.sync.aligned %0;\n" ::"n"(N) : "memory"); }
__device__ __forceinline__ void acc_fence(float* d) {
#pragma unroll
  for (int i = 0; i < 48; i++) asm volatile("" : "+f"(d[i])::"memory");
}
__device__ __forceinline__ void arrive_if(uint32_t bar) {
  asm volatile("{\n.reg .pred p;\nsetp.ne.u32 p, %0, 0;\n@p mbarrier.arrive.shared::cluster.b64 _, [%0];\n}\n" ::"r"(bar) : "memory");
}
__device__ __forceinline__ void lds128(uint32_t* v, uint32_t addr) {
  asm volatile("ld.shared.v4.b32 {%0, %1, %2, %3}, [%4];\n" : "=r"(v[0]), "=r"(v[1]), "=r"(v[2]), "=r"(v[3]) : "r"(addr) : "memory");
}
__device__ __forceinline__ void sts128(uint32_t addr, const uint32_t* v) {
  asm volatile("st.shared.v4.b32 [%0], {%1, %2, %3, %4};\n" ::"r"(addr), "r"(v[0]), "r"(v[1]), "r"(v[2]), "r"(v[3]) : "memory");
}
__device__ __forceinline__ __nv_bfloat162 as_bf2(uint32_t v) { return *reinterpret_cast<__nv_bfloat162*>(&v); }
__device__ __forceinline__ uint32_t as_u32(__nv_bfloat162 v) { return *reinterpret_cast<uint32_t*>(&v); }
__device__ __forceinline__ uint32_t hfma2(uint32_t a, uint32_t b, uint32_t c) { return as_u32(__hfma2(as_bf2(a), as_bf2(b), as_bf2(c))); }
__device__ __forceinline__ uint32_t pack2(float a, float b) { return as_u32(__floats2bfloat162_rn(a, b)); }
__device__ __forceinline__ bool elect_one() {
  uint32_t r;
  asm volatile("{\n.reg .pred p;\nelect.sync _|p, 0xffffffff;\nselp.u32 %0, 1, 0, p;\n}\n" : "=r"(r));
  return r != 0;
}
__device__ __forceinline__ void wgmma_rs(float* d, const uint32_t* a, uint64_t bdesc, int accumulate = 1) {
  asm volatile(
      "{\n.reg .pred p;\nsetp.ne.b32 p, %53, 0;\n"
      "wgmma.mma_async.sync.aligned.m64n96k16.f32.bf16.bf16 " ACC_LIST "{%48, %49, %50, %51}, %52, p, 1, 1, 1;\n}\n"
      : ACC_OPERANDS("+f", d)
      : "r"(a[0]), "r"(a[1]), "r"(a[2]), "r"(a[3]), "l"(bdesc), "r"(accumulate));
}
__device__ __forceinline__ void ldsm4(uint32_t* r, uint32_t addr) {
  asm volatile("ldmatrix.sync.aligned.m8n8.x4.shared.b16 {%0, %1, %2, %3}, [%4];\n"
               : "=r"(r[0]), "=r"(r[1]), "=r"(r[2]), "=r"(r[3])
               : "r"(addr)
               : "memory");
}
__device__ __forceinline__ void lds64(uint32_t* v, uint32_t addr) {
  asm volatile("ld.shared.v2.b32 {%0, %1}, [%2];\n" : "=r"(v[0]), "=r"(v[1]) : "r"(addr) : "memory");
}
__device__ __forceinline__ void sts32(uint32_t addr, uint32_t v) {
  asm volatile("st.shared.u32 [%0], %1;\n" ::"r"(addr), "r"(v) : "memory");
}
__device__ __forceinline__ uint32_t hadd2(uint32_t a, uint32_t b) { return as_u32(__hadd2(as_bf2(a), as_bf2(b))); }
__device__ __forceinline__ uint32_t hsub2(uint32_t a, uint32_t b) { return as_u32(__hsub2(as_bf2(a), as_bf2(b))); }
__device__ __forceinline__ uint32_t hmin2(uint32_t a, uint32_t b) { return as_u32(__hmin2(as_bf2(a), as_bf2(b))); }
__device__ __forceinline__ uint32_t hmax2(uint32_t a, uint32_t b) { return as_u32(__hmax2(as_bf2(a), as_bf2(b))); }
__device__ __forceinline__ uint32_t hfma2_lo(uint32_t w, uint32_t a, uint32_t c) {
  return as_u32(__hfma2(__low2bfloat162(as_bf2(w)), as_bf2(a), as_bf2(c)));
}
__device__ __forceinline__ uint32_t hfma2_hi(uint32_t w, uint32_t a, uint32_t c) {
  return as_u32(__hfma2(__high2bfloat162(as_bf2(w)), as_bf2(a), as_bf2(c)));
}
__device__ __forceinline__ uint32_t prmt(uint32_t a, uint32_t b, uint32_t sel) {
  uint32_t r;
  asm("prmt.b32 %0, %1, %2, %3;\n" : "=r"(r) : "r"(a), "r"(b), "r"(sel));
  return r;
}
__device__ __forceinline__ constexpr uint32_t tap_delta(int a, int b) {
  return (a == 0 ? 0xbf80u : a == 1 ? 0u : 0x3f80u) | (b == 0 ? 0xbf800000u : b == 1 ? 0u : 0x3f800000u);
}
__device__ __forceinline__ int thread_id() {
  int t;
  asm volatile("mov.u32 %0, %%tid.x;\n" : "=r"(t));
  return t;
}
__device__ __forceinline__ void proxy_fence() { asm volatile("fence.proxy.async.shared::cta;\n" ::: "memory"); }
template <int PITCH>
__device__ __forceinline__ void stage16(const float* acc, int jp, uint32_t stg) {
  uint32_t pk[4];
#pragma unroll
  for (int i = 0; i < 4; i++) pk[i] = pack2(acc[jp * 8 + i * 2], acc[jp * 8 + i * 2 + 1]);
  asm volatile("stmatrix.sync.aligned.m8n8.x4.shared.b16 [%0], {%1, %2, %3, %4};\n" ::"r"((stg ^ ((jp & 1) * 32)) + (jp >> 1) * PITCH),
               "r"(pk[0]), "r"(pk[1]), "r"(pk[2]), "r"(pk[3])
               : "memory");
}
__device__ __forceinline__ uint32_t swz(uint32_t a, uint32_t chunk) { return a | (((chunk ^ (a >> 7)) & 3) << 4); }

__device__ __forceinline__ void v_load(uint32_t (*d)[2], const uint32_t* a, uint32_t a5, uint32_t off) {
#pragma unroll
  for (int j = 0; j < 6; j++) lds64(d[j], (j == 5 ? a5 : a[j & 3]) + (j >> 2) * 4 * PLANE + off);
}
__device__ __forceinline__ void sts64_if(uint32_t addr, uint32_t a, uint32_t b, int on) {
  asm volatile("{\n.reg .pred p;\nsetp.ge.s32 p, %3, 0;\n@p st.shared.v2.b32 [%0], {%1, %2};\n}\n" ::"r"(addr), "r"(a), "r"(b), "r"(on) : "memory");
}
__device__ __forceinline__ void v_store(uint32_t (*d)[2], const uint32_t* a, uint32_t o05, uint32_t o34, uint32_t off, int on = 0) {
#pragma unroll
  for (int i = 0; i < 2; i++)
    asm volatile(
        "{\n.reg .b32 p, q, r, c;\n"
        "add.rn.bf16x2 %0, %0, %4;\n"
        "add.rn.bf16x2 %5, %5, %1;\n"
        "mov.b32 c, 0xc080c080;\n"
        "fma.rn.bf16x2 p, c, %2, %4;\n"
        "fma.rn.bf16x2 q, c, %1, %3;\n"
        "mov.b32 c, 0xc088c088;\n"
        "fma.rn.bf16x2 %0, c, %2, %0;\n"
        "fma.rn.bf16x2 %5, c, %3, %5;\n"
        "mov.b32 c, 0xbe80be80;\n"
        "fma.rn.bf16x2 r, c, %2, %4;\n"
        "fma.rn.bf16x2 %3, c, %1, %3;\n"
        "mov.b32 c, 0x3f003f00;\n"
        "fma.rn.bf16x2 %1, c, q, p;\n"
        "mov.b32 c, 0xbf00bf00;\n"
        "fma.rn.bf16x2 %2, c, q, p;\n"
        "mov.b32 c, 0x40004000;\n"
        "fma.rn.bf16x2 %4, c, %3, r;\n"
        "mov.b32 c, 0xc000c000;\n"
        "fma.rn.bf16x2 %3, c, %3, r;\n}\n"
        : "+r"(d[0][i]), "+r"(d[1][i]), "+r"(d[2][i]), "+r"(d[3][i]), "+r"(d[4][i]), "+r"(d[5][i]));
  sts64_if(a[0] + o05 + off, d[0][0], d[0][1], on);
  sts64_if(a[1] + o05 + off, d[5][0], d[5][1], on);
  sts64_if(a[2] + off, d[1][0], d[1][1], on);
  sts64_if(a[3] + off, d[2][0], d[2][1], on);
  sts64_if(a[0] + o34 + off, d[4][0], d[4][1], on);
  sts64_if(a[1] + o34 + off, d[3][0], d[3][1], on);
}
__device__ __forceinline__ void u_math16(const uint32_t (*g)[4], uint32_t dst) {
#pragma unroll
  for (int h = 0; h < 2; h++) {
    uint32_t u[2][4];
#pragma unroll
    for (int i = 0; i < 4; i++) {
      const uint32_t s = hfma2(0x3e803e80u, g[2 - h * 2][i], g[h * 2][i]);
      u[0][i] = hfma2(0x3f003f00u, g[1][i], s);
      u[1][i] = hfma2(0xbf00bf00u, g[1][i], s);
    }
    sts128(dst + h * 2 * SLOT, u[0]);
    sts128(dst + (h * 2 + 1) * SLOT, u[1]);
  }
}
__device__ __forceinline__ uint32_t u_src(int t) {
  const int c = t >= 576, q = t - c * 576, b = q >> 6, kj = (b * 11) >> 5;
  return SM_RAW + c * 3072 + kj * (6144 - 192) + b * 64 + ((q >> 2) & 15) * 192 + (q & 3) * 16;
}
__device__ __forceinline__ uint32_t u_dst(int t) { return SM_W + (t >= 576 ? 3 * SLOT : 0) + (t ^ ((t >> 3) & 3)) * 16; }

__device__ __forceinline__ void ldg128(uint32_t* v, const uint4* p) {
  asm volatile("ld.global.nc.v4.b32 {%0, %1, %2, %3}, [%4];\n" : "=r"(v[0]), "=r"(v[1]), "=r"(v[2]), "=r"(v[3]) : "l"(p));
}
__device__ __forceinline__ uint32_t lds32(uint32_t addr) {
  uint32_t v;
  asm volatile("ld.shared.u32 %0, [%1];\n" : "=r"(v) : "r"(addr) : "memory");
  return v;
}
__device__ __forceinline__ void ldsm4_if(uint32_t* r, uint32_t addr, uint32_t on) {
  asm volatile(
      "{\n.reg .pred p;\nsetp.ne.u32 p, %5, 0;\n"
      "@p ldmatrix.sync.aligned.m8n8.x4.shared.b16 {%0, %1, %2, %3}, [%4];\n}\n"
      : "+r"(r[0]), "+r"(r[1]), "+r"(r[2]), "+r"(r[3])
      : "r"(addr), "r"(on)
      : "memory");
}
__device__ __forceinline__ uint32_t hmul2_lo(uint32_t w, uint32_t a) { return as_u32(__hmul2(__low2bfloat162(as_bf2(w)), as_bf2(a))); }
__device__ __forceinline__ uint32_t clip2(uint32_t p) { return hmin2(hmax2(p, 0u), 0x435f435fu); }
__device__ __forceinline__ uint32_t frac2(uint32_t pos) {
  const float py = bf16lo(pos), px = bf16hi(pos);
  return __byte_perm(__float_as_uint(py - floorf(py)), __float_as_uint(px - floorf(px)), 0x7632);
}
__device__ __forceinline__ void coefs(uint32_t w, uint32_t& p0, uint32_t& p1) {
  const uint32_t o = hsub2(0x3f803f80u, w), xa = __byte_perm(o, w, 0x7632);
  p0 = hmul2_lo(o, xa);
  p1 = hmul2_lo(w, xa);
}
__device__ __forceinline__ uint32_t blend(uint32_t p0, uint32_t p1, uint32_t t, uint32_t g, uint32_t h, uint32_t k) {
  return hfma2_hi(p1, k, hfma2_lo(p1, h, hfma2_hi(p0, g, hmul2_lo(p0, t))));
}
__device__ __forceinline__ void st_pair(uint2* p, uint32_t a, uint32_t b) {
  asm volatile("{\n.reg .b64 v;\nmov.b64 v, {%1, %2};\nst.relaxed.gpu.global.b64 [%0], v;\n}\n" ::"l"(p), "r"(a), "r"(b) : "memory");
}
__device__ __forceinline__ void ld_pair(uint32_t* v, const uint2* p) {
  asm volatile("{\n.reg .b64 v;\nld.relaxed.gpu.global.b64 v, [%2];\nmov.b64 {%0, %1}, v;\n}\n" : "=r"(v[0]), "=r"(v[1]) : "l"(p) : "memory");
}
__device__ __forceinline__ uint32_t request(Scratch* scr, uint32_t slot, uint32_t pos, int h, int w, int tap) {
  if (slot < QUEUE) st_pair(scr->req + slot, pos, 0x80000000u | (h << 12) | (w << 4) | tap);
  return slot;
}
__device__ __forceinline__ uint32_t count_up(uint32_t addr) {
  uint32_t i;
  asm volatile("atom.shared.add.u32 %0, [%1], 1;\n" : "=r"(i) : "r"(addr) : "memory");
  return i;
}
__device__ __forceinline__ void patch(uint32_t bar, uint32_t id, uint32_t n, uint32_t base, uint32_t pitch, uint32_t ctl, int lane) {
  uint32_t todo = __ballot_sync(0xffffffffu, id < n);
#pragma unroll 1
  do {
    const int i0 = __ffs(todo) - 1;
    todo &= todo - 1;
    const uint32_t p0 = __reduce_max_sync(0xffffffffu, lane == i0 ? id : 0u), other = todo & __ballot_sync(0xffffffffu, id != p0);
    const int i1 = __ffs(other) - 1;
    todo &= ~(other & -other);
    const uint32_t p1 = __reduce_max_sync(0xffffffffu, lane == i1 ? id : 0u);
    const bool on = (lane & 15) < 12 && (lane < 16 || other);
    const uint32_t a = on ? swz(base + ((lane >> 2) & 3) * pitch + (lane < 16 ? p0 : p1) * 64, lane) : ctl + O_LST;
    uint32_t v[4], c[4];
    lds128(c, ctl + O_COR + (lane < 16 ? i0 : i1) * 192 + (lane & 15) * 16);
    mbar_wait(bar);
    lds128(v, a);
#pragma unroll
    for (int k = 0; k < 4; k++) v[k] = hadd2(v[k], c[k]);
    sts128(a, v);
    __syncwarp();
  } while (todo);
  proxy_fence();
  __syncwarp();
}

__host__ __device__ __forceinline__ int role_of(int b) {
  const int k = b >> 1;
  return b & 1 ? (k < 4 ? k + 56 : k < 60 ? k - 4 : k + 66) : k + 60;
}

struct Maps {
  CUtensorMap x, w, wc, out, off, col, gx, gout;
  CUtensorMap bx[2], bw[2], bout[2];
};

__global__ void __launch_bounds__(NTHREADS, 1)
dcn_kernel(const uint4* __restrict__ x, const uint32_t* __restrict__ offs, Scratch* __restrict__ scr, uint32_t* tsp,
           const uint32_t never, const __grid_constant__ Maps tm) {
  extern __shared__ __align__(1024) uint8_t smem[];
  constexpr uint32_t sbase = 1024;
  constexpr uint32_t bars = sbase + SM_BAR;
  const int tid = threadIdx.x;
  const int cta = role_of(blockIdx.x);
  const uint32_t tstart = clock32();
  const int wid = __shfl_sync(0xffffffffu, tid >> 5, 0);
  const int lane = tid & 31;
  const int ri = cta - NI, ry = ri / 3, x0 = 32 + (ri - ry * 3) * 64, y0 = 32 + ry * 8;
  const int band = cta >= 24, g0 = 32 + (cta - band * 24) * 8;
  if (wid == 12 && cta >= NI) {
    if (elect_one()) {
      mbar_init(bars + (B_WF + 1) * 8, 1);
      mbar_init(bars + B_XF * 8, 1);
      asm volatile("fence.mbarrier_init.release.cluster;\n" ::: "memory");
      mbar_expect_tx(bars + (B_WF + 1) * 8, 6 * SLOT);
      mbar_expect_tx(bars + B_XF * 8, UNIT);
      tma_load_3d(sbase + SM_RAW, &tm.w, bars + (B_WF + 1) * 8, 0, 0, 0);
      tma_load_3d(sbase + SM_V, &tm.x, bars + B_XF * 8, 0, x0 - 1, y0 + (ry & 1) * 4 - 1);
    }
    asm volatile("bar.arrive 0, 512;\n" ::: "memory");
  }
  if (wid == 12 && cta < NI - 4) {
    if (elect_one() && cta < 48) {
      mbar_init(bars + B_WF * 8, 1);
      mbar_init(bars + B_XF * 8, 1);
      asm volatile("fence.mbarrier_init.release.cluster;\n" ::: "memory");
      mbar_expect_tx(bars + B_WF * 8, 2 * SLOT);
      mbar_expect_tx(bars + B_XF * 8, YSLICE);
      while (clock32() - tstart < YX0) {}
      tma_load_3d(sbase + SM_YX, &tm.bx[band], bars + B_XF * 8, 0, g0 - 1, -2);
      tma_load_5d(sbase, &tm.bw[band], bars + B_WF * 8, 0, 0, 0);
      tma_load_5d(sbase + SLOT, &tm.bw[band], bars + B_WF * 8, 16, 0, 0);
    }
    asm volatile("bar.arrive 0, 512;\n" ::: "memory");
  }
  if (wid == 12 && cta >= NI - 4 && cta < NI) {
    if (elect_one()) {
#pragma unroll
      for (int c = 0; c < 5; c++) mbar_init(bars + c * 8, 1);
      asm volatile("fence.mbarrier_init.release.cluster;\n" ::: "memory");
    }
    asm volatile("bar.arrive 0, 512;\n" ::: "memory");
    if (elect_one()) {
      if (cta < NI - 1) {
#pragma unroll
        for (int c = 0; c < 4; c++) {
          mbar_expect_tx(bars + c * 8, SLOT);
          tma_load_4d(sbase + (18 + c) * SLOT, &tm.wc, bars + c * 8, (c + 2) * 24, cta - (NI - 4), 0);
        }
      } else {
        mbar_expect_tx(bars + 3 * 8, 28672 + 16128);
        tma_load_3d(sbase + 18 * SLOT, &tm.col, bars + 3 * 8, 0, 9, 0);
        bulk_load<16128>(sbase + 18 * SLOT + 28672, offs + 32 * IW * 9, bars + 3 * 8);

      }
    }
  }
  const int f = wid * 4 + (lane >> 3), g = g0 + (lane & 7);
  uint32_t o9[9];
  if (cta < 48 && wid < 8) {
    const uint32_t* op = offs + (band ? g * IW + f : f * IW + g) * 9;
#pragma unroll
    for (int a = 0; a < 3; a++)
#pragma unroll
      for (int b = 0; b < 3; b++) o9[a * 3 + b] = __ldg(op + (band ? b * 3 + a : a * 3 + b));
  }
  if (cta >= 48 && cta < NI - 4 && tid < 36) asm volatile("prefetch.global.L2 [%0];\n" ::"l"(offs + ((cta & 7) * 4 + tid / 9) * IW * 9 + tid % 9 * 32));
  if (cta >= NI - 4 && cta < NI) {
    const int kj = cta - (NI - 4);
    if (wid != 12) asm volatile("bar.sync 0, 512;\n" ::: "memory");
    auto get_epoch = [&]() {
      uint32_t e;
      asm volatile("ld.relaxed.gpu.global.u32 %0, [%1];\n" : "=r"(e) : "l"(scr->ready + (kj == 3 ? 3 : 2)) : "memory");
      return (e & ~127u) + 128;
    };
    uint32_t epoch;
    auto load_w = [&]() {
      mbar_expect_tx(bars + 4 * 8, 18 * SLOT);
#pragma unroll
      for (int sl = 0; sl < 3; sl++) tma_load_3d(sbase + sl * 6 * SLOT, &tm.w, bars + 4 * 8, 0, sl * 48, 0);
    };
    if (kj == 3) {
      constexpr uint32_t src = sbase + 18 * SLOT, lst = src + 28672 + 16128;
      uint32_t big = 0;
      epoch = get_epoch();
      if (tid < GRID) sts32(bars + 64 + tid * 4, 0);
      asm volatile("bar.sync 1, 512;\n" ::: "memory");
      if (tid == 0) load_w();
      mbar_wait(bars + 3 * 8);
#pragma unroll
      for (int i = 0; i < 6; i++) {
        const uint32_t p = tid + i * 512;
        uint32_t v[4];
        lds128(v, src + p * 16);
        const uint32_t lim = i == 0 && tid < 256 ? 0x42804080u : i >= 3 && (p - 1792 < 72 || p - 2296 < 72) ? 0x40804280u : 0x42804280u;
        uint32_t over = 0;
#pragma unroll
        for (int k = 0; k < 4; k++) over |= (v[k] & 0x7fff7fffu) + lim;
        if ((over & 0x80008000u) && (p < 1792 ? (tid & 7) < 5 : p < 2800)) big |= 1u << i;
      }
#pragma unroll 1
      for (; big; big &= big - 1) {
        const uint32_t i = count_up(bars + 64 + 57 * 4);
        if (i < 1024) sts32(lst + i * 4, tid + (__ffs(big) - 1) * 512);
      }
      __syncwarp();
      asm volatile("bar.sync 1, %0;\n" ::"r"(512 + (epoch & never)) : "memory");
      const uint32_t n = lds32(bars + 64 + 57 * 4);
      if (n > 1024 && tid < GRID && (tid < 56 || tid >= NI)) sts32(bars + 64 + tid * 4, FAILED);
#pragma unroll 1
      for (uint32_t c = tid; c < n * 4 && n <= 1024; c += 512) {
        const uint32_t wq = lds32(lst + (c & ~3u)) * 4 + (c & 3), col = wq < 7168;
        const uint32_t wi = col ? wq & 31 : wq - 7168, px = (wi * 7282) >> 16, tap = wi - px * 9;
        const int eh = col ? wq >> 5 : 32 + (px >= 224), ew = col ? 32 + px : px >= 224 ? px - 224 : px, ki = (tap * 11) >> 5;
        const uint32_t gp = pack2((float)(eh + ki - 1), (float)(ew + (int)tap - ki * 3 - 1));
        const uint32_t pos = clip2(hadd2(gp, lds32(src + wq * 4)));
        const uint32_t d = __byte_perm(hsub2(pos, hmin2(gp, 0x435f435fu)), 0, ew < 32 ? 0x1032 : 0x3210) & 0x7fff7fffu;
        if (d <= (min(eh, ew) < 32 ? 0x3f80u : 0u) || (col && (px >= 2 || eh >> 1 == 16))) continue;
        const int client = eh < 32 ? 0 : ew < 32 ? 24 : NI + ((eh - 32) >> 3) * 3 + ((ew - 32) >> 6);
        const uint32_t i = count_up(bars + 64 + client * 4);
        if (i >= MAXEX) continue;
        const uint32_t slot = count_up(bars + 64 + 56 * 4);
        const uint32_t id = eh < 32 ? eh * 8 + ew - 32 : ew < 32 ? ew * 8 + eh - 32 : (eh & 7) * 64 + ((ew - 32) & 63);
        st_pair(scr->mail[client] + i, id | (request(scr, slot < EARLY ? slot : QUEUE, pos, eh, ew, tap) << 16), epoch);
      }
      __syncwarp();
      asm volatile("bar.sync 1, %0;\n" ::"r"(512 + (epoch & never)) : "memory");
      if (tid < GRID) st_pair(scr->mail[tid] + MAXEX, lds32(bars + 64 + tid * 4), epoch);
      if (tid == 0) {
        scr->ready[3] = epoch;
        scr->ready[8 + ((epoch >> 7) & 1 ^ 1)] = 0;
      }
      TSE(2);
    } else if (wid < 12) {
      const int half = wid >= 6, q = tid - half * 192;
      const uint32_t lin = (q >> 6) * 64 + ((q >> 2) & 15) * 192 + (q & 3) * 16;
      const int e = kj * 192 + (q ^ ((q >> 3) & 3));
#pragma unroll 1
      for (int c = half - 2; c < 4; c += 2) {
        uint4 g[3], u[4];
        if (c >= 0) mbar_wait(bars + c * 8);
#pragma unroll
        for (int k = 0; k < 3; k++) lds128(&g[k].x, sbase + (18 + c) * SLOT + k * 3072 + lin);
#pragma unroll
        for (int i = 0; i < 4; i++) {
            const uint32_t s = hfma2(0x3e803e80u, (&g[2].x)[i], (&g[0].x)[i]), t = hfma2(0x3e803e80u, (&g[0].x)[i], (&g[2].x)[i]);
            (&u[0].x)[i] = hfma2(0x3f003f00u, (&g[1].x)[i], s);
            (&u[1].x)[i] = hfma2(0xbf00bf00u, (&g[1].x)[i], s);
            (&u[2].x)[i] = hfma2(0x3f003f00u, (&g[1].x)[i], t);
            (&u[3].x)[i] = hfma2(0xbf00bf00u, (&g[1].x)[i], t);
        }
        if (c >= 2) asm volatile("bar.sync 2, 416;\n" ::: "memory");
#pragma unroll
        for (int k = 0; k < 4; k++)
          asm volatile("{\n.reg .pred p;\nsetp.ge.s32 p, %5, 0;\n@p st.global.v4.b32 [%0], {%1, %2, %3, %4};\n}\n" ::"l"(scr->u + (c * 4 + k) * 576 + e),
                       "r"(u[k].x), "r"(u[k].y), "r"(u[k].z), "r"(u[k].w), "r"(c) : "memory");
        if (c >= 0) asm volatile("bar.arrive 1, 416;\n" ::: "memory");
      }
      epoch = get_epoch();
      if (!half) {
        mbar_wait(bars + 4 * 8);
#pragma unroll 6
        for (int c = 0; c < 12; c++) {
          uint4 v;
          lds128(&v.x, sbase + (c % 6 >> 1) * 6 * SLOT + (c / 6 * 6 + kj) * 6144 + (c & 1) * 3072 + lin);
          scr->w[c * 576 + e] = v;
        }
      }
      asm volatile("bar.arrive 3, %0;\n" ::"r"(512 + (epoch & never)) : "memory");
    } else if (wid == 12) {
      epoch = get_epoch();
#pragma unroll 1
      for (int r = 0; r < 3; r++) {
        asm volatile("bar.sync %0, %1;\n" ::"r"(r < 2 ? 1 : 3), "r"((r < 2 ? 416 : 512) + (epoch & never)) : "memory");
        if (elect_one()) {
          asm volatile("red.release.gpu.global.add.u32 [%0], %1;\n" ::"l"(scr->ready + r), "r"(kj ? 32 : 64) : "memory");
          if (r == 0) load_w();
        }
        __syncwarp();
        if (r == 0) asm volatile("bar.arrive 2, 416;\n" ::: "memory");
      }
    } else {
      epoch = get_epoch();
      asm volatile("bar.arrive 3, %0;\n" ::"r"(512 + (epoch & never)) : "memory");
    }
    const uint32_t dl = sbase + 18 * SLOT + 4 * 12288 + wid * 384;
#pragma unroll 1
    for (int slot = (wid == 12 ? 15 : wid > 12 ? 15 - wid : 14 - wid) * 4 + (kj ^ 3); slot < QUEUE; slot += 64) {
      uint2 rq;
#pragma unroll 1
      for (uint32_t spin = 0;; spin++) {
        uint32_t done[2];
        ld_pair(&rq.x, scr->req + slot);
        if (slot < EARLY) {
          ld_pair(done, scr->mail[56] + MAXEX);
          if (rq.y || (done[1] == epoch && slot >= done[0])) break;
        } else {
          asm volatile("ld.acquire.gpu.global.u32 %0, [%1];\n" : "=r"(done[1]) : "l"(scr->ready + 6) : "memory");
          if (rq.y) break;
          if (done[1] == epoch) {
            asm volatile("ld.relaxed.gpu.global.u32 %0, [%1];\n" : "=r"(done[0]) : "l"(scr->ready + 8 + ((epoch >> 7) & 1)) : "memory");
            if (slot - EARLY >= done[0]) break;
          }
        }
        if (spin > (1u << 22)) __trap();
        __nanosleep(100);
      }
      if (!rq.y) continue;
      __syncwarp();
      if (lane == 0) scr->req[slot] = make_uint2(0, 0);
      const int tap = rq.y & 15, ki = (tap * 11) >> 5, gy = (int)bf16lo(rq.x), gx = (int)bf16hi(rq.x);
      const int cy = min(max((int)((rq.y >> 12) & 255) + ki - 1, 0), IH - 1), cx = min(max((int)((rq.y >> 4) & 255) + tap - ki * 3 - 1, 0), IW - 1);
      if (lane < 24) {
        const uint2* pc = reinterpret_cast<const uint2*>(x) + lane;
        const int p = (gy * IW + gx) * 24, sx = gx < IW - 1 ? 24 : 0, sy = gy < IH - 1 ? IW * 24 : 0;
        const uint2 v0 = __ldg(pc + p), v1 = __ldg(pc + p + sx), v2 = __ldg(pc + p + sy), v3 = __ldg(pc + p + sy + sx);
        const uint2 c = __ldg(pc + (cy * IW + cx) * 24);
        uint32_t q0, q1;
        coefs(frac2(rq.x), q0, q1);
        const uint32_t d0 = hsub2(blend(q0, q1, v0.x, v1.x, v2.x, v3.x), c.x), d1 = hsub2(blend(q0, q1, v0.y, v1.y, v2.y, v3.y), c.y);
        const uint32_t dd[4] = {__byte_perm(d0, 0, 0x1010), __byte_perm(d0, 0, 0x3232), __byte_perm(d1, 0, 0x1010), __byte_perm(d1, 0, 0x3232)};
        sts128(dl + lane * 16, dd);
      }
      __syncwarp();
      mbar_wait(bars + 4 * 8);
      float sum[8] = {};
      const int l24 = min(lane, 23);
#pragma unroll 1
      for (int b = 0; b < 6; b++) {
        uint32_t part[4] = {};
#pragma unroll
        for (int i = 0; i < 8; i++) {
          uint32_t wv[4];
          lds128(wv, sbase + (b >> 1) * 6 * SLOT + tap * 6144 + (b & 1) * 3072 + i * 384 + l24 * 16);
          const uint32_t d = lds32(dl + (b * 16 + i * 2 + (l24 >= 12)) * 4);
#pragma unroll
          for (int k = 0; k < 4; k++) part[k] = hfma2(d, wv[k], part[k]);
        }
#pragma unroll
        for (int k = 0; k < 4; k++) {
          sum[k * 2] += bf16lo(part[k]);
          sum[k * 2 + 1] += bf16hi(part[k]);
        }
      }
#pragma unroll
      for (int k = 0; k < 8; k++) sum[k] += __shfl_down_sync(0xffffffffu, sum[k], 12);
      if (lane < 12) {
#pragma unroll
        for (int k = 0; k < 4; k++)
          st_pair(scr->res[slot] + lane * 4 + k, pack2(sum[k * 2], sum[k * 2 + 1]), epoch);
      }
      TSE(1);
    }
    mbar_wait(bars + 4 * 8);
  } else if (wid < 8) {
    const int wg = wid >> 2, warp = wid & 3;
    if (cta < 48) {
    uint32_t cf[36];
#pragma unroll
    for (int i = 0; i < 9; i++) cf[i] = o9[i];
    asm volatile("bar.sync 0, 512;\n" ::: "memory");
    {
      const uint32_t base = pack2((float)f, (float)g), sel = band ? 0x1032u : 0x3210u;
      const uint32_t tab = sbase + SM_YT + wid * 1152;
      uint32_t bad = 0;
#pragma unroll
      for (int a = 0; a < 3; a++)
#pragma unroll
        for (int b = 0; b < 3; b++) {
          const uint32_t gp = hadd2(base, tap_delta(a, b));
          const uint32_t pos = clip2(hadd2(gp, __byte_perm(cf[a * 3 + b], 0, sel)));
          uint32_t d = hsub2(pos, hmin2(gp, 0x435f435fu));
          if ((d & 0x7fff7fffu) > 0x3f80u) {
            bad = 1;
            d = a == 0 && f == 0 ? 0x3f80u : 0u;
          }
          sts32(tab + (lane & 7) * 144 + (b * 12 + (lane >> 3) * 3 + a) * 4, (d << 16) | (d & 0x8000u ? 0x3210u : 0x7654u));
        }
      if (bad && g >= 34) sts32(bars + O_CNT, FAILED);
      __syncwarp();
      arrive_if(lane == 0 ? bars + B_OS * 8 : 0u);
      asm volatile("setmaxnreg.inc.sync.aligned.u32 224;\n");
      __syncwarp();
#pragma unroll
      for (int i = 0; i < 9; i++) lds128(cf + i * 4, tab + (lane >> 2) * 144 + i * 16);
    }
    uint32_t xa[3];
#pragma unroll
    for (int b = 0; b < 3; b++)
      xa[b] = swz(sbase + SM_YX + ((wid * 4 + (lane >> 4)) * 10 + min((lane & 7) + b, IW - g0)) * 64, (lane >> 3) & 1);
    float acc[2][48];
    uint32_t X[2][16], A[2][12];
    auto fetch = [&](uint32_t* r, uint32_t a) {
#pragma unroll
      for (int i = 0; i < 4; i++) ldsm4(r + i * 4, (a ^ ((i & 1) * 32)) + i * 1280);
    };
    uint64_t bd = w_desc(sbase);
    uint32_t wf = bars + B_WF * 8;
    mbar_wait(bars + B_XF * 8);
    TSE(0);
    fetch(X[0], xa[0]);
    mbar_wait(wf);
#pragma unroll 1
    for (int s = 0; s < 3; s++) {
#pragma unroll
      for (int n = 0; n < 6; n++) {
        const int b = n >> 1;
        if (n == 5) {
          mbar_wait(bars + (B_XF + min(s + 1, 2)) * 8);
#pragma unroll
          for (int k = 0; k < 3; k++) xa[k] += s < 2 ? YSLICE : 0;
        }
        fetch(X[~n & 1], xa[(n + 1) % 6 >> 1] ^ ((~n & 1) * 32));
        const uint32_t* xr = X[n & 1];
        uint32_t D[7][2];
#pragma unroll
        for (int j = 0; j < 7; j++)
#pragma unroll
          for (int e = 0; e < 2; e++) D[j][e] = hsub2(xr[(j + 1) * 2 + e], xr[j * 2 + e]);
#pragma unroll
        for (int t = 0; t < 2; t++) {
          wgmma_wait<1>();
#pragma unroll
          for (int a = 0; a < 3; a++)
#pragma unroll
            for (int i = 0; i < 4; i++) {
              const int o = t * 2 + (i & 1), e = i >> 1, j = o + a + 1;
              const uint32_t c = cf[b * 12 + o * 3 + a];
              A[t][a * 4 + i] = hfma2_hi(c, prmt(D[j - 1][e], D[j][e], c), xr[j * 2 + e]);
            }
          wgmma_fence();
#pragma unroll
          for (int a = 0; a < 3; a++) wgmma_rs(acc[t], A[t] + a * 4, bd + n * (SLOT >> 4) + a * 192, (n | a) ? 1 : s);
          wgmma_commit();
        }
        if (n & 1) mbar_wait(wf + (b + 1) * 8);
        if (n == 1 && s == 1 && elect_one()) arrive_if(bars + B_WE * 8);
      }
      bd += 6 * SLOT >> 4;
      wf += 24;
    }
    TSE(1);
    const int lane = thread_id() & 31;
    const uint32_t stg = sbase + wg * 3 * SLOT + (wid & 3) * 2048 + (lane & 15) * 64 + ((((lane >> 4) ^ (lane >> 1)) & 3) << 4);
    wgmma_wait<1>();
    acc_fence(acc[0]);
#pragma unroll
    for (int jp = 0; jp < 6; jp++) stage16<8192>(acc[0], jp, stg);
    wgmma_wait<0>();
    acc_fence(acc[1]);
#pragma unroll
    for (int jp = 0; jp < 6; jp++) stage16<8192>(acc[1], jp, stg + 1024);
    proxy_fence();
    __syncwarp();
    arrive_if(lane == 0 ? bars + (B_ST + wg * 4) * 8 : 0u);
    } else if (cta < NI) {
      asm volatile("bar.sync 0, 512;\n" ::: "memory");
      asm volatile("setmaxnreg.inc.sync.aligned.u32 224;\n");
    } else {
    {
      uint32_t g[3][3][4], src[3], dst[3];
#pragma unroll
      for (int r = 0; r < 3; r++) {
        src[r] = sbase + u_src(tid + r * 384);
        dst[r] = sbase + u_dst(tid + r * 384);
      }
      asm volatile("bar.sync 0, 512;\n" ::: "memory");
      mbar_wait(bars + (B_WF + 1) * 8);
#pragma unroll
      for (int r = 0; r < 3; r++) {
#pragma unroll
        for (int k = 0; k < 3; k++) lds128(g[r][k], src[r] + k * 2 * SLOT);
      }
#pragma unroll
      for (int r = 0; r < 3; r++) u_math16(g[r], dst[r]);
      proxy_fence();
      __syncwarp();
      arrive_if(lane == 0 ? bars + B_WF * 8 : 0u);
    }
    asm volatile("setmaxnreg.inc.sync.aligned.u32 224;\n");
    float m[4][48];
    const uint32_t vb = sbase + SM_V + wg * UNIT;
    const uint64_t bd0 = w_desc(sbase + SM_W), ad12 = a_desc(vb + 2 * PLANE), ad05 = a_desc(vb + (wg ? 4 * PLANE : 0));

    const uint64_t d34 = wg ? -(2 * PLANE >> 4) : 2 * PLANE >> 4;
    uint64_t ad = ad12;
    uint32_t wf = bars + B_WF * 8, a[4];
    {
      const int t = thread_id();
#pragma unroll
      for (int j = 0; j < 4; j++) a[j] = swz(vb + j * PLANE + ((t & 127) >> 3) * 64, t >> 1) + (t & 1) * 8;
    }
#pragma unroll 1
    for (int sl = 0; sl < 3; sl++) {
      {
        uint32_t d[6][2], d2[6][2];
        const uint32_t a5 = y0 == 216 && ((wg ^ ry) & 1) ? a[0] : a[1], o34 = wg ? 0 : 4 * PLANE;
        mbar_wait(bars + (B_XF + sl * 2 + wg) * 8);
        if (wg | sl) mbar_wait(bars + (B_XR + sl * 2 + wg - 1) * 8);
        v_load(d, a, a5, 2048);
        v_store(d, a, 4 * PLANE - o34, o34, 2048);
        v_load(d2, a, a5, 3072);
        v_store(d2, a, 4 * PLANE - o34, o34, 3072);
        proxy_fence();
        __syncwarp();
        if (elect_one()) arrive_if(bars + (B_XR + sl * 2 + wg) * 8);
#pragma unroll
        for (int j = 0; j < 4; j++) asm volatile("add.u32 %0, %0, %1;\n" : "+r"(a[j]) : "n"(2 * UNIT));
        mbar_wait(wf);
        mbar_wait(bars + (B_XR + sl * 2 + wg) * 8);
        if (wg && sl == 2) asm volatile("bar.sync 6, 256;\n" ::: "memory");
      }
#pragma unroll
      for (int n = 0; n < 8; n++) {
        const int k = n & 3;
        wgmma_fence();
#pragma unroll
        for (int kj = 0; kj < 3; kj++)
          wgmma_ss(m[k], (k < 2 ? ad : ad + d34) + (k & 1) * (PLANE >> 4) + n / 4 * 2 + kj * 4, bd0 + n * (SLOT >> 4) + kj * 192, (n / 4 | kj) ? 1 : sl);
        wgmma_commit();
        if (n < 7) {
          if (sl) mbar_wait(wf + (n + 1) * 8);
          wgmma_wait<1>();
          if (warp == 0 && n) asm volatile("bar.arrive %0, 96;\n" ::"r"(7 + n) : "memory");
        }
      }
      if (sl == 2) asm volatile("bar.arrive %0, 256;\n" ::"r"(wg ? 4 : 6) : "memory");
      wgmma_wait<1>();
      if (warp == 0) asm volatile("bar.arrive 14, 96;\n" ::: "memory");
      wgmma_wait<0>();
      if (warp == 0) asm volatile("bar.arrive 15, 96;\n" ::: "memory");
      ad += 2 * UNIT >> 4;
      wf += 64;

    }
    const int lane = thread_id() & 31;
    const uint32_t stg = sbase + SM_X + 2 * UNIT + wg * 21504 + warp * 1024 + (lane & 15) * 64 + ((((lane >> 4) ^ (lane >> 1)) & 3) << 4);
    const uint32_t stb = lane == 0 ? bars + (B_ST + wg * 4) * 8 : 0u;
    auto publish = [&](int k) {
      proxy_fence();
      __syncwarp();
      arrive_if(stb ? stb + k * 8 : 0u);
    };
#pragma unroll
    for (int k = 0; k < 4; k++) acc_fence(m[k]);
    float dep = 0.f;
#pragma unroll
    for (int i0 = 0; i0 < 48; i0 += 8) {
      const float k0 = __uint_as_float((__float_as_uint(dep) & never) | 0xbf088889u);
      const float k1 = __uint_as_float((__float_as_uint(dep) & never) | 0xbf800000u);
#pragma unroll
      for (int i = i0; i < i0 + 8; i++) {
        m[0][i] *= k0;
        m[3][i] = fmaf(k1, m[3][i], m[2][i]);
        m[1][i] = fmaf(-8.0f / 15.0f, m[1][i], m[0][i]);
        m[2][i] = fmaf(-0.5f, m[3][i], m[2][i]);
        m[0][i] = fmaf(-0.5f, m[1][i], m[0][i]);
        m[1][i] = fmaf(4.0f / 15.0f, m[2][i], m[1][i]);
        m[0][i] = fmaf(4.0f / 15.0f, m[3][i], m[0][i]);
        m[2][i] = fmaf(0.25f, m[1][i], m[2][i]);
        m[3][i] = fmaf(0.25f, m[0][i], m[3][i]);
        dep = m[0][i];
        if ((i & 7) == 7) {
          stage16<4096>(m[2], i >> 3, stg);
          stage16<4096>(m[0], i >> 3, stg + 2 * UNIT);
        }
      }
    }
    publish(0);
    asm volatile("bar.sync %0, 256;\n" ::"r"(4 + wg) : "memory");
    const uint64_t bdx = w_desc(sbase + SM_X);
    const uint32_t s05 = vb + (wg ? 4 * PLANE : 0) + warp * 1024 + (lane & 15) * 64;
#pragma unroll
    for (int j = 0; j < 12; j++) {
      float* acc = j < 6 ? m[1] : m[3];
      const int c = j % 6;
      const uint64_t ad = ad05 + (c >> 1) * (2 * UNIT >> 4) + (c & 1) * 2 + (j < 6 ? 0 : PLANE >> 4);
      const uint64_t bd = j < 3 ? bdx + j * (SLOT >> 4) : j == 3 ? bdx + ((2 * UNIT + 12288) >> 4) : bd0 + (j - 4) * (SLOT >> 4);
      if (j != 1 && j != 2) mbar_wait(bars + (B_WF + 24 + j) * 8);
      wgmma_fence();
#pragma unroll
      for (int kj = 0; kj < 3; kj++) wgmma_ss(acc, ad + kj * 4, bd + kj * 192);
      wgmma_commit();
      if (j == 7) {
        wgmma_wait<2>();
        acc_fence(m[1]);
      }
      if (j >= 7 && j <= 9) {
#pragma unroll
        for (int jp = j * 2 - 14; jp < j * 2 - 12; jp++) stage16<2 * UNIT>(m[1], jp, swz(s05, lane >> 4));
      }
      if (j == 10) publish(1);
    }
    wgmma_wait<0>();
    acc_fence(m[3]);
    TSE(1);
#pragma unroll
    for (int jp = 0; jp < 6; jp++) stage16<2 * UNIT>(m[3], jp, swz(s05 + PLANE, lane >> 4));
    if (!wg) asm volatile("bar.arrive 5, 256;\n" ::: "memory");
    publish(2);
    }
    int rounds = 1;
    const int tid = thread_id(), lane = tid & 31;
    if (cta < 48 || cta >= NI) {
      mbar_wait(bars + B_OK * 8);
      rounds = lds32(bars + O_VER) != FAILED ? 0 : cta < 48 ? 2 : 4;
      rounds = __shfl_sync(0xffffffffu, rounds, 0);
    }
    if (rounds) {
      const bool lead = warp == 0 && elect_one();
      if (rounds > 1) {
        if (tid == 0) {
#pragma unroll
          for (int i = 0; i < 15; i++) mbar_init(bars + (B_G + i) * 8, 1);
          asm volatile("fence.mbarrier_init.release.cluster;\n" ::: "memory");
        }
        proxy_fence();
        asm volatile("bar.sync 3, 256;\n" ::: "memory");
      }
      const uint32_t win = sbase + SM_GX + wg * 3 * GSLICE, gxb = bars + (B_G + 9 + wg * 3) * 8;
      const uint64_t bd0 = w_desc(sbase);
      float acc[48];
#pragma unroll 1
      for (int r = 0; r < rounds; r++) {
        int ty, tx, bx;
        asm volatile("mov.u32 %0, %%ctaid.x;\n" : "=r"(bx));
        const int cta = role_of(bx), ry = (cta - NI) / 3, x0 = 32 + (cta - NI - ry * 3) * 64, y0 = 32 + ry * 8;
        const int band = cta >= 24, g0 = 32 + (cta - band * 24) * 8;
        if (cta >= NI) { ty = y0; tx = x0 + r * 16 + wg * 8; }
        else if (cta < 48) { ty = band ? g0 : r * 16 + wg * 8; tx = band ? r * 16 + wg * 8 : g0; }
        else { ty = (cta & 1) * 8 + wg * 16; tx = (cta & 2) * 4 + ((cta >> 2 ^ wg) & 1) * 16; }
        if (lead && rounds > 1) {
#pragma unroll 1
          for (int sl = 0; sl < 3; sl++) {
            mbar_expect_tx(gxb + sl * 8, GSLICE);
            tma_load_3d(win + sl * GSLICE, &tm.gx, gxb + sl * 8, sl * 32, tx - 2, ty - 2);
            if (r == 0) {
#pragma unroll 1
              for (int ki = 0; ki < 3; ki++) {
                if (!wg) mbar_expect_tx(bars + (B_G + sl * 3 + ki) * 8, 2 * SLOT);
                tma_load_5d(sbase + ((sl * 3 + ki) * 2 + wg) * SLOT, &tm.bw[1], bars + (B_G + sl * 3 + ki) * 8, sl * 32 + wg * 16, 0, ki);
              }
            }
          }
        }
        const int ph = ty + warp * 2 + ((lane >> 3) & 1), pw = tx + (lane & 7);
        const uint32_t* op = offs + (ph * IW + pw) * 9;
        const uint32_t base = pack2((float)ph, (float)pw);
        uint32_t ent[9], cf[36], need = 0, out = 0;
#pragma unroll
        for (int m = 0; m < 9; m++) ent[m] = __ldg(op + m);
#pragma unroll
        for (int m = 0; m < 9; m++) {
          const uint32_t pos = clip2(hadd2(hadd2(base, tap_delta(m / 3, m % 3)), ent[m])), fr = frac2(pos);
          const uint32_t iy = (int)bf16lo(pos) - (ty - 2), ix = (int)bf16hi(pos) - (tx - 2);
          out |= max(iy, ix) > 10;
          need |= ((fr >> 16 ? 1u : 0u) | (fr & 0xffffu ? 2u : 0u) | (fr >> 16 && (fr & 0xffffu) ? 4u : 0u)) << (m * 3);
          const uint32_t up = (fr & 0xffffu) >= 0x3f00u, fn = hmin2(fr, hsub2(0x3f803f80u, fr));
          const uint32_t pp = ((iy + up) * 12 + ix) * 0x10001u + (fr >= 0x3f000000u ? 1u : 0x10000u);
          ent[m] = ((pp * 64 + ((pp << 3) & 0x300030u)) ^ ((lane >> 4) * 0x100010u)) | up;
          coefs(__shfl_sync(0xffffffffu, fn, lane >> 2), cf[m * 4], cf[m * 4 + 1]);
          coefs(__shfl_sync(0xffffffffu, fn, (lane >> 2) + 8), cf[m * 4 + 2], cf[m * 4 + 3]);
        }
        need = __reduce_or_sync(0xffffffffu, need);
        asm volatile("{\n.reg .pred p;\nsetp.ne.u32 p, %0, 0;\nbarrier.red.popc.u32 %0, %1, 128, p;\n}\n" : "+r"(out) : "r"(1 + wg) : "memory");
        out = __shfl_sync(0xffffffffu, out, 0);
        TSE(0);
        if (!out) {
          uint32_t C[2][4][8], A[2][8];
#pragma unroll
          for (int i = 0; i < 64; i++) C[0][0][i] = 0;
          auto fetch = [&](uint32_t (*c)[8], int m, uint32_t slice) {
            const uint32_t a0 = (ent[m] & 0xfff0u) + slice, a1 = (ent[m] >> 16) + slice, dy = 768 - (ent[m] & 1) * 1536;
#pragma unroll
            for (int h = 0; h < 2; h++) {
              ldsm4(c[0] + h * 4, a0 ^ (h * 32));
              ldsm4_if(c[1] + h * 4, a1 ^ (h * 32), need & (1 << (m * 3)));
              ldsm4_if(c[2] + h * 4, (a0 ^ (h * 32) ^ 32) + dy, need & (2 << (m * 3)));
              ldsm4_if(c[3] + h * 4, (a1 ^ (h * 32) ^ 32) + dy, need & (4 << (m * 3)));
            }
          };
#pragma unroll 1
          for (int sl = 0; sl < 3; sl++) {
            const uint32_t slice = win + sl * GSLICE;
            const uint64_t bd = bd0 + sl * (6 * SLOT >> 4);
            mbar_wait(gxb + sl * 8, r & 1);
            fetch(C[0], 0, slice);
#pragma unroll
            for (int m = 0; m < 9; m++) {
              if (m < 8) fetch(C[~m & 1], m + 1, slice);
              if (m % 3 == 0) mbar_wait(bars + (B_G + sl * 3 + m / 3) * 8);
              if (m >= 2) wgmma_wait<1>();
#pragma unroll
              for (int i = 0; i < 8; i++)
                A[m & 1][i] = blend(cf[m * 4 + (i & 1) * 2], cf[m * 4 + (i & 1) * 2 + 1], C[m & 1][0][i], C[m & 1][1][i], C[m & 1][2][i], C[m & 1][3][i]);
              wgmma_fence();
              wgmma_rs(acc, A[m & 1], bd + m / 3 * (2 * SLOT >> 4) + m % 3 * 192, m ? 1 : sl);
              wgmma_rs(acc, A[m & 1] + 4, bd + (m / 3 * 2 + 1) * (SLOT >> 4) + m % 3 * 192);
              wgmma_commit();
            }
            wgmma_wait<0>();
          }
        } else {
#pragma unroll 1
          for (int i = 0; i < 12; i++) mbar_wait(i < 9 ? bars + (B_G + i) * 8 : gxb + (i - 9) * 8, i < 9 ? 0 : r & 1);
          const uint32_t scratch = win + warp * 3072 + lane * 16;
#pragma unroll 1
          for (int m = 0; m < 9; m++) {
            const int ki = (m * 11) >> 5;
            const uint32_t pos = clip2(hadd2(pack2((float)(ph + ki - 1), (float)(pw + m - ki * 3 - 1)), __ldg(op + m)));
            const int gy = (int)bf16lo(pos), gx = (int)bf16hi(pos), sx = gx < IW - 1 ? 12 : 0, sy = gy < IH - 1 ? IW * 12 : 0;
            const uint4* pc = x + (gy * IW + gx) * 12 + (lane >> 4);
            uint32_t q0, q1, V[6][4][4], A[6][4];
            coefs(frac2(pos), q0, q1);
#pragma unroll
            for (int k = 0; k < 6; k++)
#pragma unroll
              for (int c = 0; c < 4; c++) ldg128(V[k][c], pc + k * 2 + (c & 1) * sx + (c >> 1) * sy);
#pragma unroll
            for (int k = 0; k < 6; k++) {
#pragma unroll
              for (int i = 0; i < 4; i++) V[k][0][i] = blend(q0, q1, V[k][0][i], V[k][1][i], V[k][2][i], V[k][3][i]);
              sts128(scratch + k * 512, V[k][0]);
            }
            __syncwarp();
#pragma unroll
            for (int k = 0; k < 6; k++) ldsm4(A[k], scratch + k * 512);
            wgmma_fence();
#pragma unroll
            for (int k = 0; k < 6; k++) wgmma_rs(acc, A[k], bd0 + ((k >> 1) * 6 + ki * 2 + (k & 1)) * (SLOT >> 4) + (m - ki * 3) * 192, k ? 1 : m);
            wgmma_commit();
            wgmma_wait<0>();
          }
        }
        acc_fence(acc);
        TSE(1);
        asm volatile("bar.sync %0, 128;\n" ::"r"(1 + wg) : "memory");
#pragma unroll
        for (int jp = 0; jp < 6; jp++) stage16<4096>(acc, jp, win + warp * 1024 + (lane & 15) * 64 + ((((lane >> 4) ^ (lane >> 1)) & 3) << 4));
        proxy_fence();
        asm volatile("bar.sync %0, 128;\n" ::"r"(1 + wg) : "memory");
        if (lead) {
          tma_store(&tm.gout, win, tx, ty);
          asm volatile("cp.async.bulk.commit_group;\ncp.async.bulk.wait_group.read 0;\n" ::: "memory");
          TSE(2);
        }
      }
    }
  } else if (wid < 12) {
    asm volatile("setmaxnreg.dec.sync.aligned.u32 32;\n");
    const int tid = thread_id(), lane = tid & 31;

    const bool one = elect_one();
    if (one && cta < NI) {
#pragma unroll
      for (int i = 0; i < 4; i++) mbar_init(bars + (B_G + (wid - 8) * 4 + i) * 8, 1);
      asm volatile("fence.mbarrier_init.release.cluster;\n" ::: "memory");
    }
    if (one && cta >= NI) {
#pragma unroll
      for (int i = 0; i < 7; i++) mbar_init(bars + (B_WF + 8 + (wid - 8) * 7 + i) * 8, 1);
      if (wid == 8) mbar_init(bars + B_WF * 8, 12);
      mbar_init(bars + (B_UR + wid - 8) * 8, 1);
      asm volatile("fence.mbarrier_init.release.cluster;\n" ::: "memory");
    }
    asm volatile("bar.arrive 3, 256;\n" ::: "memory");
    asm volatile("bar.sync 0, 512;\n" ::: "memory");
    if (cta >= NI) {
      uint32_t a[4], d[1][6][2];
#pragma unroll
      for (int j = 0; j < 4; j++) a[j] = swz(sbase + SM_V + j * PLANE + ((tid & 127) >> 3) * 64, lane >> 1) + (lane & 1) * 8;
      const bool bot = y0 == 216;
      uint32_t off = 0;
#pragma unroll 1
      for (int u = -1; u < 6; u++) {
        const uint32_t a5 = bot && ((u ^ ry) & 1) ? a[0] : a[1], o34 = u & 1 ? 0 : 4 * PLANE;
        if (u >= 0) mbar_wait(bars + (B_XF + u) * 8);
#pragma unroll 1
        for (int i = 0; i < (u < 0 ? 0 : (u & 3) == (wid & 3) ? 3 : 2); i++) {
          const uint32_t h = off + (i < 2 ? i * 1024 : 4096 - (wid & 2) * 256);
          v_load(d[0], a, a5, i == 2 && (lane & 16 || (x0 == 160 && lane >= 8)) ? h - (lane >> 3) * 64 : h);
          v_store(d[0], a, 4 * PLANE - o34, o34, h, i == 2 && lane >= 16 ? -1 : u);
        }
        if (u < 0) {
      mbar_wait(bars + (B_WF + 1) * 8);
#pragma unroll 1
      for (int t = tid; t < 1152; t += 384) {
        uint32_t g[3][4];
        const uint32_t src = sbase + u_src(t);
#pragma unroll
        for (int k = 0; k < 3; k++) lds128(g[k], src + k * 2 * SLOT);
        u_math16(g, sbase + u_dst(t));
      }
      proxy_fence();
      __syncwarp();
      arrive_if(one ? bars + B_WF * 8 : 0u);
          continue;
        }
        proxy_fence();
        __syncwarp();
        arrive_if(one ? bars + (B_XR + u) * 8 : 0u);
        off += UNIT + ((u ^ wid) & 1 ? -256 : 256);
      }
    }
  } else {
    asm volatile("setmaxnreg.dec.sync.aligned.u32 32;\n");
    const int tid = thread_id(), lane = tid & 31;
    const bool one = elect_one();
    if (wid != 12) {
      if (one) {
        if (cta >= NI) {
          if (wid == 13) {
#pragma unroll
            for (int i = 0; i < 6; i++) mbar_init(bars + (B_XR + i) * 8, 8);
          } else if (wid == 15) {
#pragma unroll
            for (int i = 1; i < 6; i++) mbar_init(bars + (B_XF + i) * 8, 1);
          }
        } else {
#pragma unroll
          for (int i = 0; i < 3; i++) mbar_init(bars + (B_WF + 1 + (wid - 13) * 3 + i) * 8, 1);
          if (wid == 13) mbar_init(bars + B_WE * 8, 8);
          if (wid < 15) mbar_init(bars + (B_XF + wid - 12) * 8, 1);
        }
        if (wid == 14) {
#pragma unroll
          for (int i = 0; i < 8; i++) mbar_init(bars + (B_ST + i) * 8, 4);
#pragma unroll
          for (int i = B_OF; i <= B_OK; i++) mbar_init(bars + i * 8, i != B_OS ? 1 : cta < NI ? 8 : 2);
          sts32(bars + O_CNT, 0);
        }
        asm volatile("fence.mbarrier_init.release.cluster;\n" ::: "memory");
      }
      asm volatile("bar.arrive 3, 256;\n" ::: "memory");
      asm volatile("bar.sync 0, 512;\n" ::: "memory");
      if (cta >= 48 && cta < NI) {
        if (wid == 15 && one) asm volatile("red.relaxed.gpu.global.add.u32 [%0], 1;\n" ::"l"(scr->ready + 6) : "memory");
      } else {
        uint32_t epoch = 0;
        if (cta >= NI && wid < 15) {
          const uint32_t lim = (pack2((float)max(y0, 34) - 1.5f, (float)max(x0, 34) - 1.5f) & 0x7f807f80u) - 0x04000400u;
          uint32_t big = 0;
          mbar_wait(bars + B_OF * 8);
#pragma unroll 1
          for (int i0 = 0; i0 < 18; i0 += 6) {
            uint32_t v[6][4];
#pragma unroll
            for (int i = 0; i < 6; i++) lds128(v[i], sbase + SM_OFF + (tid - 416) * 16 + (i0 + i) * 1024);
            __nv_bfloat162 mx = as_bf2(0u), mn = as_bf2(0u);
#pragma unroll
            for (int i = 0; i < 6 * 2; i++) {
              mx = __hmax2_nan(__hmax2_nan(mx, as_bf2(v[i >> 1][(i & 1) * 2])), as_bf2(v[i >> 1][(i & 1) * 2 + 1]));
              mn = __hmin2_nan(__hmin2_nan(mn, as_bf2(v[i >> 1][(i & 1) * 2])), as_bf2(v[i >> 1][(i & 1) * 2 + 1]));
            }
            big |= __hblt2(__hmax2_nan(mx, __hneg2(mn)), as_bf2(lim)) ? 0u : 1u << i0;
          }
          __syncwarp();
          arrive_if(one ? bars + B_OS * 8 : 0u);
          if (wid == 13) {
            mbar_wait(bars + B_OS * 8);
            mbar_wait(bars + (B_WF + 12) * 8);
            if (one) {
              mbar_expect_tx(bars + (B_XF + 5) * 8, UNIT);
              tma_load_3d(sbase + SM_V + 5 * UNIT, &tm.x, bars + (B_XF + 5) * 8, 64, x0 - 1, y0 + (~ry & 1) * 4 - 1);
            }
          }
#pragma unroll 1
          for (uint32_t who; (who = __ballot_sync(0xffffffffu, big)) != 0;) {
            const int src = __ffs(who) - 1;
            const uint32_t b = __reduce_or_sync(0xffffffffu, lane == src ? big : 0u);
            if (lane == src) big &= big - 1;
            const uint32_t wi = ((wid - 13) * 32 + src + (__ffs(b) - 1 + (lane >> 2)) * 64) * 4 + (lane & 3), id = (wi * 7282) >> 16, tap = wi - id * 9;
            const int ki = (tap * 11) >> 5, h = y0 + (id >> 6), w = x0 + (id & 63);
            mbar_wait(bars + B_EP * 8);
            epoch = lds32(bars + O_EPO);
            if (lds32(bars + O_CNT) > MAXEX) big = 0;
            if (lane < 24 && h >= 34 && w >= 34) {
              const uint32_t gp = pack2((float)(h + ki - 1), (float)(w + (int)tap - ki * 3 - 1));
              const uint32_t pos = clip2(hadd2(gp, __ldg(offs + (h * IW + w) * 9 + tap)));
              if (pos != hmin2(gp, 0x435f435fu)) {
                const uint32_t i = count_up(bars + O_CNT);
                if (i < MAXEX)
                  sts32(bars + O_LST + i * 4, id | (request(scr, min(atomicAdd(scr->ready + 8 + ((epoch >> 7) & 1), 1u) + EARLY, QUEUE), pos, h, w, tap) << 16));
              }
            }
            __syncwarp();
          }
          if (wid == 14) asm volatile("bar.arrive 7, 64;\n" ::: "memory");
        }
        if (wid == 13) {
          uint32_t m[2] = {}, cnt = 0;
          mbar_wait(bars + B_EP * 8);
          epoch = lds32(bars + O_EPO);
          if (cta >= NI ? x0 == 32 || y0 == 32 : g0 == 32) {
#pragma unroll 1
            for (uint32_t spin = 0;; spin++) {
              ld_pair(m, scr->mail[cta] + min(lane, MAXEX));
              const uint32_t have = __ballot_sync(0xffffffffu, m[1] == epoch);
              cnt = __reduce_max_sync(0xffffffffu, lane == MAXEX ? m[0] : 0u);
              if ((have >> MAXEX) && (cnt > MAXEX || !(~have & ((1u << cnt) - 1)))) break;
              if (spin > (1u << 22)) __trap();
            }
          }
          if (cta >= NI) asm volatile("bar.sync 7, 64;\n" ::: "memory");
          else mbar_wait(bars + B_OS * 8);
          if (one) asm volatile("red.relaxed.gpu.global.add.u32 [%0], 1;\n" ::"l"(scr->ready + 6) : "memory");
          const uint32_t own = lds32(bars + O_CNT);
          if (own && lane >= cnt) m[0] = lds32(bars + O_LST + ((lane - cnt) & 15) * 4);
          cnt += own;
          if (cnt > MAXEX || __any_sync(0xffffffffu, lane < cnt && m[0] >> 16 == QUEUE)) cnt = FAILED;
          const uint32_t id = lane < cnt ? m[0] & 511 : 512;
          const uint32_t rows = cnt == FAILED ? FAILED : __reduce_or_sync(0xffffffffu, lane < cnt ? 1u << (id >> (cta < NI ? 7 : 6)) : 0u);
          if (one) sts32(bars + O_VER, rows);
          __syncwarp();
          arrive_if(one ? bars + B_OK * 8 : 0u);
          TSE(0);
#pragma unroll 1
          for (uint32_t got = 0; got < cnt && cnt != FAILED; got += 4) {
            const uint32_t i = min(got + (lane >> 3), cnt - 1);
            const uint2* r = scr->res[__shfl_sync(0xffffffffu, m[0], i) >> 16] + (lane & 7);
            uint32_t v[12];
#pragma unroll 1
            for (uint32_t spin = 0;; spin++) {
              uint32_t miss = 0;
#pragma unroll
              for (int k = 0; k < 6; k++) ld_pair(v + k * 2, r + k * 8);
#pragma unroll
              for (int k = 0; k < 6; k++) miss |= v[k * 2 + 1] ^ epoch;
              if (__all_sync(0xffffffffu, !miss)) break;
              if (spin > (1u << 22)) __trap();
            }
#pragma unroll
            for (int k = 0; k < 6; k++) sts32(bars + O_COR + i * 192 + (lane & 7) * 4 + k * 32, v[k * 2]);
          }
          __syncwarp();
#pragma unroll 1
          for (int i = cnt && cnt != FAILED ? -1 : 8; i < 8; i++) {
            const int t = (i >> 1) & 1, r = (i & 1) + ((i >> 1) & 2), row = cta < NI ? i : ((t ^ ry) & 1) * 4 + ((2 - r) & 3);
            if (i >= 0 && !((rows >> row) & 1)) continue;
            const uint32_t base = cta < NI ? sbase + (i & 1) * 3 * SLOT
                                           : r < 2 ? sbase + SM_X + (2 + r * 2) * UNIT + t * 21504 : sbase + SM_V + t * (UNIT + 4 * PLANE) + (r - 2) * PLANE;
            const uint32_t pitch = cta < NI ? 8192 : r < 2 ? 4096 : 2 * UNIT;
            patch(bars + (i < 0 ? B_OK : B_ST + (cta < NI ? i * 4 : t * 4 + max(r - 1, 0))) * 8, i < 0 ? lane ? 512 : 0 : id - (row << (cta < NI ? 7 : 6)),
                  cta < NI ? 128 : 64, base, pitch, bars, i < 0 ? 12 : lane);
            if (one && i >= 0) {
              if (cta < NI) {
                tma_store(&tm.bout[band], base, g0, i * 16);
              } else {
#pragma unroll
                for (int k = 0; k < 3; k++) tma_store3(&tm.out, base + k * pitch, k * 32, x0, y0 + row);
              }
            }
          }
          if (one) asm volatile("cp.async.bulk.commit_group;\ncp.async.bulk.wait_group.read 0;\n" ::: "memory");
          TSE(2);
        } else {
          if (wid == 15) {
            auto poll = [&]() {
              uint32_t v;
              asm volatile("ld.acquire.gpu.global.u32 %0, [%1];\n" : "=r"(v) : "l"(scr->ready + min(lane, 6)) : "memory");
              return v;
            };
            const uint32_t epoch = (__reduce_max_sync(0xffffffffu, lane == 6 ? poll() : 0u) & ~127u) + 128;
            if (one) sts32(bars + O_EPO, epoch);
            arrive_if(one ? bars + B_EP * 8 : 0u);
            if (cta >= NI) {
              uint32_t seen = 0;
              wait_until(tstart, POLLT);
#pragma unroll 1
              for (uint32_t spin = 0; seen != 7; spin++) {
                const uint32_t now = __ballot_sync(0xffffffffu, poll() == epoch) & ~seen & 7;
                if (now) {
                  asm volatile("fence.proxy.async.global;\n" ::: "memory");
                  arrive_if((now >> lane) & 1 ? bars + (B_UR + lane) * 8 : 0u);
                  seen |= now;
                }
                if (spin > (1u << 22)) __trap();
              }
            }
          }
          const int t = wid & 1;
          mbar_wait(bars + B_OK * 8);
          const int r0 = cta < NI ? t : ((t ^ ry) & 1) * 4;
          const uint32_t skip = __shfl_sync(0xffffffffu, lds32(bars + O_VER), 0) >> r0;
          if (cta < NI) {
            mbar_wait(bars + (B_ST + t * 4) * 8);
            if (one && !(skip & 1)) tma_store(&tm.bout[band], sbase + t * 3 * SLOT, g0, t * 16);
          } else {
#pragma unroll
            for (int r = 0; r < 4; r++) {
              const uint32_t base = r < 2 ? sbase + SM_X + (2 + r * 2) * UNIT + t * 21504 : sbase + SM_V + t * (UNIT + 4 * PLANE) + (r - 2) * PLANE;
              if (r != 1) mbar_wait(bars + (B_ST + t * 4 + max(r - 1, 0)) * 8);
              if (r == 1) mbar_wait(bars + (B_UR + 3) * 8);
              if (!((skip >> ((2 - r) & 3)) & 1)) {
#pragma unroll
                for (int k = 0; k < 3; k++)
                  if (one) tma_store3(&tm.out, base + k * (r < 2 ? 4096 : 2 * UNIT), k * 32, x0, y0 + r0 + ((2 - r) & 3));
              }
            }
          }
          if (one) asm volatile("cp.async.bulk.commit_group;\ncp.async.bulk.wait_group.read 0;\n" ::: "memory");
          TSE(2);
        }
      }
    } else if (cta < NI) {
        auto load_x = [&](int s) {
          mbar_expect_tx(bars + (B_XF + s) * 8, YSLICE);
          tma_load_3d(sbase + SM_YX + s * YSLICE, &tm.bx[band], bars + (B_XF + s) * 8, s * 32, g0 - 1, -2);
        };
        auto load_w = [&](int p) {
          const int s = (p * 11) >> 5, b = p - s * 3;
          mbar_expect_tx(bars + (B_WF + p) * 8, 2 * SLOT);
#pragma unroll
          for (int h = 0; h < 2; h++)
            tma_load_5d(sbase + (p * 2 + h) * SLOT, &tm.bw[band], bars + (B_WF + p) * 8, s * 32 + h * 16, band ? 0 : b, band ? b : 0);
        };
        asm volatile("bar.sync 3, 256;\n" ::: "memory");
        if (one && cta >= 48) {
#pragma unroll 1
          for (int sl = 0; sl < 3; sl++) {
            wait_until(tstart, sl * GDT);
#pragma unroll
            for (int wg = 0; wg < 2; wg++) {
              mbar_expect_tx(bars + (B_G + 9 + wg * 3 + sl) * 8, GSLICE);
              tma_load_3d(sbase + SM_GX + (wg * 3 + sl) * GSLICE, &tm.gx, bars + (B_G + 9 + wg * 3 + sl) * 8, sl * 32,
                          (cta & 2) * 4 + ((cta >> 2 ^ wg) & 1) * 16 - 2, (cta & 1) * 8 + wg * 16 - 2);
            }
#pragma unroll 1
            for (int i = 0; i < 6; i++) {
              if (!(i & 1)) mbar_expect_tx(bars + (B_G + sl * 3 + (i >> 1)) * 8, 2 * SLOT);
              tma_load_5d(sbase + (sl * 6 + i) * SLOT, &tm.bw[1], bars + (B_G + sl * 3 + (i >> 1)) * 8, sl * 32 + (i & 1) * 16, 0, i >> 1);
            }
          }
        }
        if (one && cta < 48) {
          arrive_if(bars + (B_WF + 9) * 8);
#pragma unroll 1
          for (int p = 1; p < 9; p++) {
            wait_until(tstart, YWT + (p - 1) * YWDT);
            if (p == 3) load_x(1);
            if (p == 6) load_x(2);
            if (p == 8) mbar_wait(bars + B_WE * 8);
            load_w(p);
          }
        }
    } else {
        auto load_x = [&](int u) {
          mbar_expect_tx(bars + (B_XF + u) * 8, UNIT);
          tma_load_3d(sbase + SM_V + u * UNIT, &tm.x, bars + (B_XF + u) * 8, (u >> 1) * 32, x0 - 1, y0 + ((u ^ ry) & 1) * 4 - 1);
        };
        asm volatile("bar.sync 3, 256;\n" ::: "memory");
        if (lane < 28) mbar_expect_tx(bars + (B_WF + 8 + lane) * 8, lane == 16 ? 3 * SLOT : lane == 17 || lane == 18 ? 0 : SLOT);
        if (smem_u32(smem) != sbase) __trap();
#pragma unroll 1
        for (int xu = 1; xu <= 3; xu++) {
          wait_until(tstart, XT1 + (xu - 1) * XDT);
          if (xu == 3) mbar_wait(bars + B_WF * 8);
          if (one) load_x(xu);
          if (xu == 3 && one) {
            mbar_expect_tx(bars + B_OF * 8, 2 * SLOT);
            tma_load_3d(sbase + SM_OFF, &tm.off, bars + B_OF * 8, 0, x0 * 9 / 32, y0);
          }
        }
        const uint4* src = scr->u;
        uint32_t fb = bars + (B_WF + 8) * 8;
#pragma unroll 1
        for (int q = 0; q < 6; q++) {
          mbar_wait(bars + (B_UR + (q >> 1)) * 8);
          if (q == 4) {
            if (one) bulk_load<3 * SLOT>(sbase + SM_X, src, fb);
            if (one) bulk_load<SLOT>(sbase + SM_X + 2 * UNIT + 12288, src + 3 * 576, fb + 24);
            src += 4 * 576;
            fb += 32;
          }
          const uint32_t dst = sbase + SM_W + (q & 1) * 4 * SLOT, id = 8 + (q & 1) * 4;
#pragma unroll
          for (int k = 0; k < 4; k++) {
            asm volatile("bar.sync %0, 96;\n" ::"r"(id + k) : "memory");
            if (one) bulk_load<SLOT>(dst + k * SLOT, src + k * 576, fb + k * 8);
            if (k == 3 && q == 5 && one) arrive_if(bars + (B_UR + 3) * 8);
          }
          if (q == 1 && one) load_x(4);
          src += 4 * 576;
          fb += 32;
        }
    }
  }
}

typedef CUresult (*EncodeTiledFn)(CUtensorMap*, CUtensorMapDataType, cuuint32_t, void*, const cuuint64_t*,
                                  const cuuint64_t*, const cuuint32_t*, const cuuint32_t*, CUtensorMapInterleave,
                                  CUtensorMapSwizzle, CUtensorMapL2promotion, CUtensorMapFloatOOBfill);

}

extern "C" void kernel_launch(void* const* d_in, const int* in_sizes, int n_in, void* d_out, int out_size) {
  static EncodeTiledFn encode = nullptr;
  static Scratch* scratch = nullptr;
  if (!encode) {
    void* fn = nullptr;
    cudaDriverEntryPointQueryResult qres;
    cudaGetDriverEntryPoint("cuTensorMapEncodeTiled", &fn, cudaEnableDefault, &qres);
    encode = (EncodeTiledFn)fn;
    cudaGetSymbolAddress((void**)&scratch, g_scratch);
    cudaFuncSetAttribute(dcn_kernel, cudaFuncAttributeMaxDynamicSharedMemorySize, SMEM_BYTES);
  }
  uint32_t* tsp = nullptr;
  Maps tm;
  auto make = [&](CUtensorMap* m, void* p, int rank, const cuuint64_t* dims, const cuuint64_t* strides, const cuuint32_t* box, bool swizzle) {
    const cuuint32_t es[5] = {1, 1, 1, 1, 1};
    encode(m, CU_TENSOR_MAP_DATA_TYPE_BFLOAT16, rank, p, dims, strides, box, es, CU_TENSOR_MAP_INTERLEAVE_NONE,
           swizzle ? CU_TENSOR_MAP_SWIZZLE_64B : CU_TENSOR_MAP_SWIZZLE_NONE, CU_TENSOR_MAP_L2_PROMOTION_NONE,
           CU_TENSOR_MAP_FLOAT_OOB_FILL_NONE);
  };
  const cuuint64_t PX = IC * 2, ROW = IW * IC * 2, TAP = IC * IC * 2;
  for (int t = 0; t < 2; t++) {
    const cuuint64_t dims[3] = {IC, IW, IH}, odims[4] = {32, IW, IH, 3}, strides[3] = {t ? ROW : PX, t ? PX : ROW, 64};
    const cuuint32_t xb[3] = {32, 66, 6}, ob[3] = {32, 64, 1}, bxb[3] = {32, 10, 36}, bob[4] = {32, 8, 16, 3};
    if (!t) make(&tm.x, d_in[0], 3, dims, strides, xb, true);
    if (!t) make(&tm.out, d_out, 3, dims, strides, ob, true);
    const cuuint32_t gxb[3] = {32, 12, 12}, gob[4] = {32, 8, 8, 3};
    if (!t) make(&tm.gx, d_in[0], 3, dims, strides, gxb, true);
    if (!t) make(&tm.gout, d_out, 4, odims, strides, gob, true);
    make(&tm.bx[t], d_in[0], 3, dims, strides, bxb, true);
    make(&tm.bout[t], d_out, 4, odims, strides, bob, true);
    const cuuint64_t wdims[5] = {32, IC, 3, 3, 3}, wstrides[4] = {PX, 64, TAP, 3 * TAP};
    const cuuint32_t wb[5] = {32, 16, 3, t ? 3u : 1u, t ? 1u : 3u};
    make(&tm.bw[t], d_in[2], 5, wdims, wstrides, wb, true);
  }
  {
    const cuuint64_t dims[3] = {64, 144, 9}, strides[2] = {128, TAP};
    const cuuint32_t box[3] = {64, 48, 9};
    make(&tm.w, d_in[2], 3, dims, strides, box, false);
    const cuuint64_t cdims[4] = {64, 144, 3, 3}, cstrides[3] = {128, TAP, 3 * TAP};
    const cuuint32_t cbox[4] = {64, 24, 1, 3};
    make(&tm.wc, d_in[2], 4, cdims, cstrides, cbox, false);
    const cuuint64_t odims[3] = {64, 63, IH}, ostrides[2] = {128, IW * 36};
    const cuuint32_t obox[3] = {64, 18, 8};
    make(&tm.off, d_in[1], 3, odims, ostrides, obox, false);
    const cuuint32_t cb[3] = {64, 1, IH};
    make(&tm.col, d_in[1], 3, odims, ostrides, cb, false);
  }
  dcn_kernel<<<GRID, NTHREADS, SMEM_BYTES>>>((const uint4*)d_in[0], (const uint32_t*)d_in[1], scratch, tsp, 0u, tm);
}
```

```cpp
#include <cuda_runtime.h>
#include <cuda.h>
#include <cuda_bf16.h>
#include <stdint.h>

namespace {

constexpr int IH = 224, IW = 224, IC = 96;
constexpr int GRID = 132, NTHREADS = 512;
constexpr int NI = 60;
constexpr int SLOT = 9216;
constexpr int SMEM_BYTES = 232448;
constexpr int PLANE = 66 * 64, UNIT = 6 * PLANE;
constexpr int SM_V = 256, SM_X = SM_V + 2 * PLANE, SM_W = 36 * PLANE + 512, SM_BAR = SM_W + 8 * SLOT;
constexpr int SM_RAW = SM_V + 3 * UNIT, SM_OFF = SM_V + 6 * UNIT - 2 * SLOT;
constexpr int YSLICE = 36 * 10 * 64, SM_YX = 16 * SLOT, SM_YT = SM_YX + 3 * YSLICE;
constexpr int GSLICE = 144 * 64, SM_GX = 18 * SLOT;
constexpr int B_WF = 0, B_WE = 36, B_XF = 60, B_XR = 66, B_ST = 72, B_UR = 80, B_OF = 84, B_OS = 85, B_EP = 86, B_OK = 87, B_G = 88;
constexpr int O_CNT = 832, O_VER = 848, O_EPO = 852, O_LST = 864, O_COR = 1024;
constexpr int MAXEX = 16, EARLY = 128, QUEUE = 192;
constexpr uint32_t FAILED = 0xffff;
#define PACE XT1 = 2500, XDT = 900, POLLT = 4600, YX0 = 1400, YWT = 3800, YWDT = 1100, GDT = 3500
constexpr uint32_t PACE;
#define EARLYW 1
#define FLIP 0
#define PFM 0
#define LOCK 1
#define PDR 1
#define PUB1 10
#define HAND 12
#define BUB 0
#define CPF 0
#define X5W 8
#define WAT 0
#define TG 8
#define OFFAT 3
#define X4Q 1

#define CSLEEP 1500
#define X1T 1800
#define CG 2
#define SH 0x121212
#define BSLEEP 2200

struct Scratch {
  uint4 u[16 * SLOT / 16];
  uint4 w[12 * SLOT / 16];
  uint32_t ready[32];
  uint2 req[QUEUE];
  uint2 res[QUEUE][48];
  uint2 mail[GRID][32];
};
__device__ __align__(128) Scratch g_scratch;

#define TQ(i)
#define TSE(i)

__device__ __forceinline__ float bf16lo(uint32_t v) { return __uint_as_float(v << 16); }
__device__ __forceinline__ float bf16hi(uint32_t v) { return __uint_as_float(v & 0xffff0000u); }
__device__ __forceinline__ uint32_t smem_u32(const void* p) { return (uint32_t)__cvta_generic_to_shared(p); }
__device__ __forceinline__ void mbar_init(uint32_t bar, uint32_t count) {
  asm volatile("mbarrier.init.shared::cta.b64 [%0], %1;\n" ::"r"(bar), "r"(count) : "memory");
}
__device__ __forceinline__ void mbar_expect_tx(uint32_t bar, uint32_t bytes) {
  asm volatile("mbarrier.arrive.expect_tx.shared::cta.b64 _, [%0], %1;\n" ::"r"(bar), "r"(bytes) : "memory");
}
__device__ __forceinline__ void mbar_wait(uint32_t bar, uint32_t parity = 0) {
  uint32_t done;
#pragma unroll 1
  for (uint32_t spin = 0; spin < (1u << 22); spin++) {
    asm volatile(
        "{\n.reg .pred p;\n"
        "mbarrier.try_wait.parity.shared::cta.b64 p, [%1], %2;\n"
        "selp.u32 %0, 1, 0, p;\n}\n"
        : "=r"(done)
        : "r"(bar), "r"(parity)
        : "memory");
    if (done) return;
  }
  __trap();
}
__device__ __forceinline__ uint32_t clock32() {
  uint32_t c;
  asm volatile("mov.u32 %0, %%clock;\n" : "=r"(c)::"memory");
  return c;
}
__device__ __forceinline__ void wait_until(uint32_t t0, uint32_t dt) {
  while (clock32() - t0 < dt) __nanosleep(50);
}
__device__ __forceinline__ void tma_load_3d(uint32_t dst, const CUtensorMap* tm, uint32_t bar, int c0, int c1, int c2) {
  asm volatile(
      "cp.async.bulk.tensor.3d.shared::cluster.global.mbarrier::complete_tx::bytes [%0], [%1, {%3, %4, %5}], [%2];\n" ::"r"(dst),
      "l"(reinterpret_cast<uint64_t>(tm)), "r"(bar), "r"(c0), "r"(c1), "r"(c2)
      : "memory");
}
__device__ __forceinline__ void tma_load_5d(uint32_t dst, const CUtensorMap* tm, uint32_t bar, int c, int kj, int ki) {
  asm volatile(
      "cp.async.bulk.tensor.5d.shared::cluster.global.mbarrier::complete_tx::bytes [%0], [%1, {%3, %4, %3, %5, %6}], [%2];\n" ::"r"(dst),
      "l"(reinterpret_cast<uint64_t>(tm)), "r"(bar), "r"(0), "r"(c), "r"(kj), "r"(ki)
      : "memory");
}
__device__ __forceinline__ void tma_load_4d(uint32_t dst, const CUtensorMap* tm, uint32_t bar, int c1, int c2, int c3) {
  asm volatile(
      "cp.async.bulk.tensor.4d.shared::cluster.global.mbarrier::complete_tx::bytes [%0], [%1, {%3, %4, %5, %6}], [%2];\n" ::"r"(dst),
      "l"(reinterpret_cast<uint64_t>(tm)), "r"(bar), "r"(0), "r"(c1), "r"(c2), "r"(c3)
      : "memory");
}
template <int BYTES>
__device__ __forceinline__ void bulk_load(uint32_t dst, const void* src, uint32_t bar) {
  asm volatile("cp.async.bulk.shared::cluster.global.mbarrier::complete_tx::bytes [%0], [%1], %3, [%2];\n" ::"r"(dst), "l"(src),
               "r"(bar), "n"(BYTES)
               : "memory");
}
__device__ __forceinline__ void tma_store3(const CUtensorMap* tm, uint32_t src, int c0, int c1, int c2) {
  asm volatile("cp.async.bulk.tensor.3d.global.shared::cta.bulk_group [%0, {%2, %3, %4}], [%1];\n" ::"l"(
                   reinterpret_cast<uint64_t>(tm)),
               "r"(src), "r"(c0), "r"(c1), "r"(c2)
               : "memory");
}
__device__ __forceinline__ void tma_store(const CUtensorMap* tm, uint32_t src, int c1, int c2) {
  asm volatile("cp.async.bulk.tensor.4d.global.shared::cta.bulk_group [%0, {%2, %3, %4, %2}], [%1];\n" ::"l"(
                   reinterpret_cast<uint64_t>(tm)),
               "r"(src), "r"(0), "r"(c1), "r"(c2)
               : "memory");
}
__device__ __forceinline__ uint64_t w_desc(uint32_t saddr) {
  return (uint64_t)((saddr & 0x3FFFF) >> 4) | ((uint64_t)(1024 >> 4) << 16) | ((uint64_t)(512 >> 4) << 32) | ((uint64_t)2 << 62);
}
__device__ __forceinline__ uint64_t a_desc(uint32_t saddr) {
  return (uint64_t)((saddr & 0x3FFFF) >> 4) | ((uint64_t)1 << 16) | ((uint64_t)(512 >> 4) << 32) | ((uint64_t)2 << 62);
}
#define ACC_OPERANDS(c, d)                                                                                        \
  c(d[0]), c(d[1]), c(d[2]), c(d[3]), c(d[4]), c(d[5]), c(d[6]), c(d[7]), c(d[8]),      \
      c(d[9]), c(d[10]), c(d[11]), c(d[12]), c(d[13]), c(d[14]), c(d[15]), c(d[16]),       \
      c(d[17]), c(d[18]), c(d[19]), c(d[20]), c(d[21]), c(d[22]), c(d[23]), c(d[24]),      \
      c(d[25]), c(d[26]), c(d[27]), c(d[28]), c(d[29]), c(d[30]), c(d[31]), c(d[32]),      \
      c(d[33]), c(d[34]), c(d[35]), c(d[36]), c(d[37]), c(d[38]), c(d[39]), c(d[40]),      \
      c(d[41]), c(d[42]), c(d[43]), c(d[44]), c(d[45]), c(d[46]), c(d[47])
#define ACC_LIST                                                                   \
  "{%0, %1, %2, %3, %4, %5, %6, %7, %8, %9, %10, %11, %12, %13, %14, %15, "        \
  "%16, %17, %18, %19, %20, %21, %22, %23, %24, %25, %26, %27, %28, %29, %30, %31, " \
  "%32, %33, %34, %35, %36, %37, %38, %39, %40, %41, %42, %43, %44, %45, %46, %47}, "
__device__ __forceinline__ void wgmma_ss(float* d, uint64_t adesc, uint64_t bdesc, int accumulate = 1) {
  asm volatile(
      "{\n.reg .pred p;\nsetp.ne.b32 p, %50, 0;\n"
      "wgmma.mma_async.sync.aligned.m64n96k16.f32.bf16.bf16 " ACC_LIST "%48, %49, p, 1, 1, 0, 1;\n}\n"
      : ACC_OPERANDS("+f", d)
      : "l"(adesc), "l"(bdesc), "r"(accumulate));
}
__device__ __forceinline__ void wgmma_fence() { asm volatile("wgmma.fence.sync.aligned;\n" ::: "memory"); }
__device__ __forceinline__ void wgmma_commit() { asm volatile("wgmma.commit_group.sync.aligned;\n" ::: "memory"); }
template <int N>
__device__ __forceinline__ void wgmma_wait() { asm volatile("wgmma.wait_group.sync.aligned %0;\n" ::"n"(N) : "memory"); }
__device__ __forceinline__ void acc_fence(float* d) {
#pragma unroll
  for (int i = 0; i < 48; i++) asm volatile("" : "+f"(d[i])::"memory");
}
__device__ __forceinline__ void arrive_if(uint32_t bar) {
  asm volatile("{\n.reg .pred p;\nsetp.ne.u32 p, %0, 0;\n@p mbarrier.arrive.shared::cluster.b64 _, [%0];\n}\n" ::"r"(bar) : "memory");
}
__device__ __forceinline__ void lds128(uint32_t* v, uint32_t addr) {
  asm volatile("ld.shared.v4.b32 {%0, %1, %2, %3}, [%4];\n" : "=r"(v[0]), "=r"(v[1]), "=r"(v[2]), "=r"(v[3]) : "r"(addr) : "memory");
}
__device__ __forceinline__ void sts128(uint32_t addr, const uint32_t* v) {
  asm volatile("st.shared.v4.b32 [%0], {%1, %2, %3, %4};\n" ::"r"(addr), "r"(v[0]), "r"(v[1]), "r"(v[2]), "r"(v[3]) : "memory");
}
__device__ __forceinline__ __nv_bfloat162 as_bf2(uint32_t v) { return *reinterpret_cast<__nv_bfloat162*>(&v); }
__device__ __forceinline__ uint32_t as_u32(__nv_bfloat162 v) { return *reinterpret_cast<uint32_t*>(&v); }
__device__ __forceinline__ uint32_t hfma2(uint32_t a, uint32_t b, uint32_t c) { return as_u32(__hfma2(as_bf2(a), as_bf2(b), as_bf2(c))); }
__device__ __forceinline__ uint32_t pack2(float a, float b) { return as_u32(__floats2bfloat162_rn(a, b)); }
__device__ __forceinline__ bool elect_one() {
  uint32_t r;
  asm volatile("{\n.reg .pred p;\nelect.sync _|p, 0xffffffff;\nselp.u32 %0, 1, 0, p;\n}\n" : "=r"(r));
  return r != 0;
}
__device__ __forceinline__ void wgmma_rs(float* d, const uint32_t* a, uint64_t bdesc, int accumulate = 1) {
  asm volatile(
      "{\n.reg .pred p;\nsetp.ne.b32 p, %53, 0;\n"
      "wgmma.mma_async.sync.aligned.m64n96k16.f32.bf16.bf16 " ACC_LIST "{%48, %49, %50, %51}, %52, p, 1, 1, 1;\n}\n"
      : ACC_OPERANDS("+f", d)
      : "r"(a[0]), "r"(a[1]), "r"(a[2]), "r"(a[3]), "l"(bdesc), "r"(accumulate));
}
__device__ __forceinline__ void ldsm4(uint32_t* r, uint32_t addr) {
  asm volatile("ldmatrix.sync.aligned.m8n8.x4.shared.b16 {%0, %1, %2, %3}, [%4];\n"
               : "=r"(r[0]), "=r"(r[1]), "=r"(r[2]), "=r"(r[3])
               : "r"(addr)
               : "memory");
}
__device__ __forceinline__ void lds64(uint32_t* v, uint32_t addr) {
  asm volatile("ld.shared.v2.b32 {%0, %1}, [%2];\n" : "=r"(v[0]), "=r"(v[1]) : "r"(addr) : "memory");
}
__device__ __forceinline__ void sts32(uint32_t addr, uint32_t v) {
  asm volatile("st.shared.u32 [%0], %1;\n" ::"r"(addr), "r"(v) : "memory");
}
__device__ __forceinline__ uint32_t hadd2(uint32_t a, uint32_t b) { return as_u32(__hadd2(as_bf2(a), as_bf2(b))); }
__device__ __forceinline__ uint32_t hsub2(uint32_t a, uint32_t b) { return as_u32(__hsub2(as_bf2(a), as_bf2(b))); }
__device__ __forceinline__ uint32_t hmin2(uint32_t a, uint32_t b) { return as_u32(__hmin2(as_bf2(a), as_bf2(b))); }
__device__ __forceinline__ uint32_t hmax2(uint32_t a, uint32_t b) { return as_u32(__hmax2(as_bf2(a), as_bf2(b))); }
__device__ __forceinline__ uint32_t hfma2_lo(uint32_t w, uint32_t a, uint32_t c) {
  return as_u32(__hfma2(__low2bfloat162(as_bf2(w)), as_bf2(a), as_bf2(c)));
}
__device__ __forceinline__ uint32_t hfma2_hi(uint32_t w, uint32_t a, uint32_t c) {
  return as_u32(__hfma2(__high2bfloat162(as_bf2(w)), as_bf2(a), as_bf2(c)));
}
__device__ __forceinline__ uint32_t prmt(uint32_t a, uint32_t b, uint32_t sel) {
  uint32_t r;
  asm("prmt.b32 %0, %1, %2, %3;\n" : "=r"(r) : "r"(a), "r"(b), "r"(sel));
  return r;
}
__device__ __forceinline__ constexpr uint32_t tap_delta(int a, int b) {
  return (a == 0 ? 0xbf80u : a == 1 ? 0u : 0x3f80u) | (b == 0 ? 0xbf800000u : b == 1 ? 0u : 0x3f800000u);
}
__device__ __forceinline__ int thread_id() {
  int t;
  asm volatile("mov.u32 %0, %%tid.x;\n" : "=r"(t));
  return t ^ FLIP;
}
__device__ __forceinline__ void proxy_fence() { asm volatile("fence.proxy.async.shared::cta;\n" ::: "memory"); }
template <int PITCH>
__device__ __forceinline__ void stage16(const float* acc, int jp, uint32_t stg) {
  uint32_t pk[4];
#pragma unroll
  for (int i = 0; i < 4; i++) pk[i] = pack2(acc[jp * 8 + i * 2], acc[jp * 8 + i * 2 + 1]);
  asm volatile("stmatrix.sync.aligned.m8n8.x4.shared.b16 [%0], {%1, %2, %3, %4};\n" ::"r"((stg ^ ((jp & 1) * 32)) + (jp >> 1) * PITCH),
               "r"(pk[0]), "r"(pk[1]), "r"(pk[2]), "r"(pk[3])
               : "memory");
}
__device__ __forceinline__ uint32_t swz(uint32_t a, uint32_t chunk) { return a | (((chunk ^ (a >> 7)) & 3) << 4); }

__device__ __forceinline__ void v_load(uint32_t (*d)[2], const uint32_t* a, uint32_t a5, uint32_t off) {
#pragma unroll
  for (int j = 0; j < 6; j++) lds64(d[j], (j == 5 ? a5 : a[j & 3]) + (j >> 2) * 4 * PLANE + off);
}
__device__ __forceinline__ void sts64_if(uint32_t addr, uint32_t a, uint32_t b, int on) {
  asm volatile("{\n.reg .pred p;\nsetp.ge.s32 p, %3, 0;\n@p st.shared.v2.b32 [%0], {%1, %2};\n}\n" ::"r"(addr), "r"(a), "r"(b), "r"(on) : "memory");
}
__device__ __forceinline__ void v_store(uint32_t (*d)[2], const uint32_t* a, uint32_t o05, uint32_t o34, uint32_t off, int on = 0) {
#pragma unroll
  for (int i = 0; i < 2; i++)
    asm volatile(
        "{\n.reg .b32 p, q, r, c;\n"
        "add.rn.bf16x2 %0, %0, %4;\n"
        "add.rn.bf16x2 %5, %5, %1;\n"
        "mov.b32 c, 0xc080c080;\n"
        "fma.rn.bf16x2 p, c, %2, %4;\n"
        "fma.rn.bf16x2 q, c, %1, %3;\n"
        "mov.b32 c, 0xc088c088;\n"
        "fma.rn.bf16x2 %0, c, %2, %0;\n"
        "fma.rn.bf16x2 %5, c, %3, %5;\n"
        "mov.b32 c, 0xbe80be80;\n"
        "fma.rn.bf16x2 r, c, %2, %4;\n"
        "fma.rn.bf16x2 %3, c, %1, %3;\n"
        "mov.b32 c, 0x3f003f00;\n"
        "fma.rn.bf16x2 %1, c, q, p;\n"
        "mov.b32 c, 0xbf00bf00;\n"
        "fma.rn.bf16x2 %2, c, q, p;\n"
        "mov.b32 c, 0x40004000;\n"
        "fma.rn.bf16x2 %4, c, %3, r;\n"
        "mov.b32 c, 0xc000c000;\n"
        "fma.rn.bf16x2 %3, c, %3, r;\n}\n"
        : "+r"(d[0][i]), "+r"(d[1][i]), "+r"(d[2][i]), "+r"(d[3][i]), "+r"(d[4][i]), "+r"(d[5][i]));
  sts64_if(a[0] + o05 + off, d[0][0], d[0][1], on);
  sts64_if(a[1] + o05 + off, d[5][0], d[5][1], on);
  sts64_if(a[2] + off, d[1][0], d[1][1], on);
  sts64_if(a[3] + off, d[2][0], d[2][1], on);
  sts64_if(a[0] + o34 + off, d[4][0], d[4][1], on);
  sts64_if(a[1] + o34 + off, d[3][0], d[3][1], on);
}
__device__ __forceinline__ void u_math16(const uint32_t (*g)[4], uint32_t dst) {
#pragma unroll
  for (int h = 0; h < 2; h++) {
    uint32_t u[2][4];
#pragma unroll
    for (int i = 0; i < 4; i++) {
      const uint32_t s = hfma2(0x3e803e80u, g[2 - h * 2][i], g[h * 2][i]);
      u[0][i] = hfma2(0x3f003f00u, g[1][i], s);
      u[1][i] = hfma2(0xbf00bf00u, g[1][i], s);
    }
    sts128(dst + h * 2 * SLOT, u[0]);
    sts128(dst + (h * 2 + 1) * SLOT, u[1]);
  }
}
__device__ __forceinline__ uint32_t u_src(int t) {
  const int c = t >= 576, q = t - c * 576, b = q >> 6, kj = (b * 11) >> 5;
  return SM_RAW + c * 3072 + kj * (6144 - 192) + b * 64 + ((q >> 2) & 15) * 192 + (q & 3) * 16;
}
__device__ __forceinline__ uint32_t u_dst(int t) { return SM_W + (t >= 576 ? 3 * SLOT : 0) + (t ^ ((t >> 3) & 3)) * 16; }

__device__ __forceinline__ void ldg128(uint32_t* v, const uint4* p) {
  asm volatile("ld.global.nc.v4.b32 {%0, %1, %2, %3}, [%4];\n" : "=r"(v[0]), "=r"(v[1]), "=r"(v[2]), "=r"(v[3]) : "l"(p));
}
__device__ __forceinline__ uint32_t lds32(uint32_t addr) {
  uint32_t v;
  asm volatile("ld.shared.u32 %0, [%1];\n" : "=r"(v) : "r"(addr) : "memory");
  return v;
}
__device__ __forceinline__ void ldsm4_if(uint32_t* r, uint32_t addr, uint32_t on) {
  asm volatile(
      "{\n.reg .pred p;\nsetp.ne.u32 p, %5, 0;\n"
      "@p ldmatrix.sync.aligned.m8n8.x4.shared.b16 {%0, %1, %2, %3}, [%4];\n}\n"
      : "+r"(r[0]), "+r"(r[1]), "+r"(r[2]), "+r"(r[3])
      : "r"(addr), "r"(on)
      : "memory");
}
__device__ __forceinline__ uint32_t hmul2_lo(uint32_t w, uint32_t a) { return as_u32(__hmul2(__low2bfloat162(as_bf2(w)), as_bf2(a))); }
__device__ __forceinline__ uint32_t clip2(uint32_t p) { return hmin2(hmax2(p, 0u), 0x435f435fu); }
__device__ __forceinline__ uint32_t frac2(uint32_t pos) {
  const float py = bf16lo(pos), px = bf16hi(pos);
  return __byte_perm(__float_as_uint(py - floorf(py)), __float_as_uint(px - floorf(px)), 0x7632);
}
__device__ __forceinline__ void coefs(uint32_t w, uint32_t& p0, uint32_t& p1) {
  const uint32_t o = hsub2(0x3f803f80u, w), xa = __byte_perm(o, w, 0x7632);
  p0 = hmul2_lo(o, xa);
  p1 = hmul2_lo(w, xa);
}
__device__ __forceinline__ uint32_t blend(uint32_t p0, uint32_t p1, uint32_t t, uint32_t g, uint32_t h, uint32_t k) {
  return hfma2_hi(p1, k, hfma2_lo(p1, h, hfma2_hi(p0, g, hmul2_lo(p0, t))));
}
__device__ __forceinline__ void st_pair(uint2* p, uint32_t a, uint32_t b) {
  asm volatile("{\n.reg .b64 v;\nmov.b64 v, {%1, %2};\nst.relaxed.gpu.global.b64 [%0], v;\n}\n" ::"l"(p), "r"(a), "r"(b) : "memory");
}
__device__ __forceinline__ void ld_pair(uint32_t* v, const uint2* p) {
  asm volatile("{\n.reg .b64 v;\nld.relaxed.gpu.global.b64 v, [%2];\nmov.b64 {%0, %1}, v;\n}\n" : "=r"(v[0]), "=r"(v[1]) : "l"(p) : "memory");
}
__device__ __forceinline__ uint32_t request(Scratch* scr, uint32_t slot, uint32_t pos, int h, int w, int tap) {
  if (slot < QUEUE) st_pair(scr->req + slot, pos, 0x80000000u | (h << 12) | (w << 4) | tap);
  return slot;
}
__device__ __forceinline__ uint32_t count_up(uint32_t addr) {
  uint32_t i;
  asm volatile("atom.shared.add.u32 %0, [%1], 1;\n" : "=r"(i) : "r"(addr) : "memory");
  return i;
}
__device__ __forceinline__ void patch(uint32_t bar, uint32_t id, uint32_t n, uint32_t base, uint32_t pitch, uint32_t ctl, int lane) {
  uint32_t todo = __ballot_sync(0xffffffffu, id < n);
#pragma unroll 1
  do {
    const int i0 = __ffs(todo) - 1;
    todo &= todo - 1;
    const uint32_t p0 = __reduce_max_sync(0xffffffffu, lane == i0 ? id : 0u), other = todo & __ballot_sync(0xffffffffu, id != p0);
    const int i1 = __ffs(other) - 1;
    todo &= ~(other & -other);
    const uint32_t p1 = __reduce_max_sync(0xffffffffu, lane == i1 ? id : 0u);
    const bool on = (lane & 15) < 12 && (lane < 16 || other);
    const uint32_t a = on ? swz(base + ((lane >> 2) & 3) * pitch + (lane < 16 ? p0 : p1) * 64, lane) : ctl + O_LST;
    uint32_t v[4], c[4];
    lds128(c, ctl + O_COR + (lane < 16 ? i0 : i1) * 192 + (lane & 15) * 16);
    mbar_wait(bar);
    lds128(v, a);
#pragma unroll
    for (int k = 0; k < 4; k++) v[k] = hadd2(v[k], c[k]);
    sts128(a, v);
    __syncwarp();
  } while (todo);
  proxy_fence();
  __syncwarp();
}

__host__ __device__ __forceinline__ int role_of(int b) {
  const int k = b >> 1;
  return b & 1 ? (k < 4 ? k + 56 : k < 60 ? k - 4 : k + 66) : k + 60;
}

__device__ __forceinline__ int low_bits(const void* p) {
  int r;
  asm volatile("{\n.reg .b32 h;\nmov.b64 {%0, h}, %1;\nand.b32 %0, %0, 15;\n}\n" : "=r"(r) : "l"(p));
  return r;
}
struct Maps {
  Scratch* scr;
  CUtensorMap x, w, wc, out, off, col, gx, gout;
  CUtensorMap bx[2], bw[2], bout[2];
};

__global__ void __launch_bounds__(NTHREADS, 1)
dcn_kernel(const uint4* __restrict__ x, const uint32_t* __restrict__ offs, uint32_t* tsp,
           const uint32_t never, const __grid_constant__ Maps tm) {
  extern __shared__ __align__(1024) uint8_t smem[];
  constexpr uint32_t sbase = 1024;
  constexpr uint32_t bars = sbase + SM_BAR;
  const uint32_t tstart = clock32();
  const int tid = thread_id();
  if (PFM == 1 || PFM == 2) asm volatile("prefetch.tensormap [%0];\n" ::"l"(reinterpret_cast<uint64_t>(&tm.w)) : "memory");
  if (PFM == 2) asm volatile("prefetch.tensormap [%0];\n" ::"l"(reinterpret_cast<uint64_t>(&tm.x)) : "memory");
  const int wid = __shfl_sync(0xffffffffu, (tid >> 5) + (PFM == 3 ? low_bits(&tm.w) : 0), 0);
  const bool first = wid == 12 && (!(blockIdx.x & 1) || blockIdx.x >= 120);
  if (EARLYW && first && elect_one()) {
    mbar_init(bars + (B_WF + 1) * 8, 1);
    tma_load_3d(sbase + SM_RAW, &tm.w, bars + (B_WF + 1) * 8, 0, 0, 0);
  }
  int bx = blockIdx.x;
  if (EARLYW) asm volatile("mov.u32 %0, %%ctaid.x;\n" : "=r"(bx));
  const int cta = role_of(bx);
  const int lane = tid & 31;
  const int ri = cta - NI, ry = ri / 3, x0 = 32 + (ri - ry * 3) * 64, y0 = 32 + ry * 8;
  const int band = cta >= 24, g0 = 32 + (cta - band * 24) * 8;
  if (first) {
    const bool one = elect_one();
    if (one) {
      if (!EARLYW) mbar_init(bars + (B_WF + 1) * 8, 1);
      mbar_init(bars + B_XF * 8, 1);
      mbar_init(bars + (B_XF + 1) * 8, 1);
      asm volatile("fence.mbarrier_init.release.cluster;\n" ::: "memory");
      if (!EARLYW) tma_load_3d(sbase + SM_RAW, &tm.w, bars + (B_WF + 1) * 8, 0, 0, 0);
      tma_load_3d(sbase + SM_V, &tm.x, bars + B_XF * 8, 0, x0 - 1, y0 + (ry & 1) * 4 - 1);
      mbar_expect_tx(bars + (B_WF + 1) * 8, 6 * SLOT);
      mbar_expect_tx(bars + B_XF * 8, UNIT);
      mbar_expect_tx(bars + (B_XF + 1) * 8, UNIT);
    }
    asm volatile("bar.arrive 0, 512;\n" ::: "memory");
    if (one) {
      while (clock32() - tstart < X1T) {}
      tma_load_3d(sbase + SM_V + UNIT, &tm.x, bars + (B_XF + 1) * 8, 0, x0 - 1, y0 + (~ry & 1) * 4 - 1);
    }
  }
  if (wid == 12 && cta >= NI - 4 && cta < NI) {
    if (elect_one()) {
#pragma unroll
      for (int c = 0; c < 5; c++) mbar_init(bars + c * 8, 1);
      asm volatile("fence.mbarrier_init.release.cluster;\n" ::: "memory");
    }
    asm volatile("bar.arrive 0, 512;\n" ::: "memory");
    if (elect_one()) {
      if (cta < NI - 1) {
#pragma unroll
        for (int c = 0; c < 4; c++) {
          mbar_expect_tx(bars + c * 8, SLOT);
          tma_load_4d(sbase + (18 + c) * SLOT, &tm.wc, bars + c * 8, (c + 2) * 24, cta - (NI - 4), 0);
        }
      } else {
        mbar_expect_tx(bars + 3 * 8, 28672 + 16128);
        tma_load_3d(sbase + 18 * SLOT, &tm.col, bars + 3 * 8, 0, 9, 0);
        bulk_load<16128>(sbase + 18 * SLOT + 28672, offs + 32 * IW * 9, bars + 3 * 8);

      }
    }
  }
  if (cta >= NI - 4 && cta < NI) {
    const int kj = cta - (NI - 4);
    if (wid != 12) asm volatile("bar.sync 0, 512;\n" ::: "memory");
    auto get_epoch = [&]() {
      uint32_t e;
      asm volatile("ld.relaxed.gpu.global.u32 %0, [%1];\n" : "=r"(e) : "l"(tm.scr->ready + (kj == 3 ? 3 : 2)) : "memory");
      return (e & ~127u) + 128;
    };
    uint32_t epoch;
    auto load_w = [&]() {
      mbar_expect_tx(bars + 4 * 8, 18 * SLOT);
#pragma unroll
      for (int sl = 0; sl < 3; sl++) tma_load_3d(sbase + sl * 6 * SLOT, &tm.w, bars + 4 * 8, 0, sl * 48, 0);
    };
    if (kj == 3) {
      constexpr uint32_t src = sbase + 18 * SLOT, lst = src + 28672 + 16128;
      uint32_t big = 0;
      epoch = get_epoch();
      if (tid < GRID) sts32(bars + 64 + tid * 4, 0);
      asm volatile("bar.sync 1, 512;\n" ::: "memory");
      if (tid == 0) load_w();
      mbar_wait(bars + 3 * 8);
#pragma unroll
      for (int i = 0; i < 6; i++) {
        const uint32_t p = tid + i * 512;
        uint32_t v[4];
        lds128(v, src + p * 16);
        const uint32_t lim = i == 0 && tid < 256 ? 0x42804080u : i >= 3 && (p - 1792 < 72 || p - 2296 < 72) ? 0x40804280u : 0x42804280u;
        uint32_t over = 0;
#pragma unroll
        for (int k = 0; k < 4; k++) over |= (v[k] & 0x7fff7fffu) + lim;
        if ((over & 0x80008000u) && (p < 1792 ? (tid & 7) < 5 : p < 2800)) big |= 1u << i;
      }
#pragma unroll 1
      for (; big; big &= big - 1) {
        const uint32_t i = count_up(bars + 64 + 57 * 4);
        if (i < 1024) sts32(lst + i * 4, tid + (__ffs(big) - 1) * 512);
      }
      __syncwarp();
      asm volatile("bar.sync 1, %0;\n" ::"r"(512 + (epoch & never)) : "memory");
      const uint32_t n = lds32(bars + 64 + 57 * 4);
      if (n > 1024 && tid < GRID && (tid < 56 || tid >= NI)) sts32(bars + 64 + tid * 4, FAILED);
#pragma unroll 1
      for (uint32_t c = tid; c < n * 4 && n <= 1024; c += 512) {
        const uint32_t wq = lds32(lst + (c & ~3u)) * 4 + (c & 3), col = wq < 7168;
        const uint32_t wi = col ? wq & 31 : wq - 7168, px = (wi * 7282) >> 16, tap = wi - px * 9;
        const int eh = col ? wq >> 5 : 32 + (px >= 224), ew = col ? 32 + px : px >= 224 ? px - 224 : px, ki = (tap * 11) >> 5;
        const uint32_t gp = pack2((float)(eh + ki - 1), (float)(ew + (int)tap - ki * 3 - 1));
        const uint32_t pos = clip2(hadd2(gp, lds32(src + wq * 4)));
        const uint32_t d = __byte_perm(hsub2(pos, hmin2(gp, 0x435f435fu)), 0, ew < 32 ? 0x1032 : 0x3210) & 0x7fff7fffu;
        if (d <= (min(eh, ew) < 32 ? 0x3f80u : 0u) || (col && (px >= 2 || eh >> 1 == 16))) continue;
        const int client = eh < 32 ? 0 : ew < 32 ? 24 : NI + ((eh - 32) >> 3) * 3 + ((ew - 32) >> 6);
        const uint32_t i = count_up(bars + 64 + client * 4);
        if (i >= MAXEX) continue;
        const uint32_t slot = count_up(bars + 64 + 56 * 4);
        const uint32_t id = eh < 32 ? eh * 8 + ew - 32 : ew < 32 ? ew * 8 + eh - 32 : (eh & 7) * 64 + ((ew - 32) & 63);
        st_pair(tm.scr->mail[client] + i, id | (request(tm.scr, slot < EARLY ? slot : QUEUE, pos, eh, ew, tap) << 16), epoch);
      }
      __syncwarp();
      asm volatile("bar.sync 1, %0;\n" ::"r"(512 + (epoch & never)) : "memory");
      if (tid < GRID) st_pair(tm.scr->mail[tid] + MAXEX, lds32(bars + 64 + tid * 4), epoch);
      if (tid == 0) {
        tm.scr->ready[3] = epoch;
        tm.scr->ready[8 + ((epoch >> 7) & 1 ^ 1)] = 0;
      }
      TSE(2);
    } else if (wid < 12) {
      const int half = wid >= 6, q = tid - half * 192;
      const uint32_t lin = (q >> 6) * 64 + ((q >> 2) & 15) * 192 + (q & 3) * 16;
      const int e = kj * 192 + (q ^ ((q >> 3) & 3));
#pragma unroll 1
      for (int c = half - 2; c < 4; c += 2) {
        uint4 g[3], u[4];
        if (c >= 0) mbar_wait(bars + c * 8);
#pragma unroll
        for (int k = 0; k < 3; k++) lds128(&g[k].x, sbase + (18 + c) * SLOT + k * 3072 + lin);
#pragma unroll
        for (int i = 0; i < 4; i++) {
            const uint32_t s = hfma2(0x3e803e80u, (&g[2].x)[i], (&g[0].x)[i]), t = hfma2(0x3e803e80u, (&g[0].x)[i], (&g[2].x)[i]);
            (&u[0].x)[i] = hfma2(0x3f003f00u, (&g[1].x)[i], s);
            (&u[1].x)[i] = hfma2(0xbf00bf00u, (&g[1].x)[i], s);
            (&u[2].x)[i] = hfma2(0x3f003f00u, (&g[1].x)[i], t);
            (&u[3].x)[i] = hfma2(0xbf00bf00u, (&g[1].x)[i], t);
        }
        if (c >= 2) asm volatile("bar.sync 2, 416;\n" ::: "memory");
#pragma unroll
        for (int k = 0; k < 4; k++)
          asm volatile("{\n.reg .pred p;\nsetp.ge.s32 p, %5, 0;\n@p st.global.v4.b32 [%0], {%1, %2, %3, %4};\n}\n" ::"l"(tm.scr->u + (c * 4 + k) * 576 + e),
                       "r"(u[k].x), "r"(u[k].y), "r"(u[k].z), "r"(u[k].w), "r"(c) : "memory");
        if (c >= 0) asm volatile("bar.arrive 1, 416;\n" ::: "memory");
      }
      epoch = get_epoch();
      if (!half) {
        mbar_wait(bars + 4 * 8);
#pragma unroll 6
        for (int c = 0; c < 12; c++) {
          uint4 v;
          lds128(&v.x, sbase + (c % 6 >> 1) * 6 * SLOT + (c / 6 * 6 + kj) * 6144 + (c & 1) * 3072 + lin);
          tm.scr->w[c * 576 + e] = v;
        }
      }
      asm volatile("bar.arrive 3, %0;\n" ::"r"(512 + (epoch & never)) : "memory");
    } else if (wid == 12) {
      epoch = get_epoch();
#pragma unroll 1
      for (int r = 0; r < 3; r++) {
        asm volatile("bar.sync %0, %1;\n" ::"r"(r < 2 ? 1 : 3), "r"((r < 2 ? 416 : 512) + (epoch & never)) : "memory");
        if (elect_one()) {
          asm volatile("red.release.gpu.global.add.u32 [%0], %1;\n" ::"l"(tm.scr->ready + r), "r"(kj ? 32 : 64) : "memory");
          if (r == WAT) load_w();
        }
        __syncwarp();
        if (r == 0) asm volatile("bar.arrive 2, 416;\n" ::: "memory");
      }
    } else {
      epoch = get_epoch();
      asm volatile("bar.arrive 3, %0;\n" ::"r"(512 + (epoch & never)) : "memory");
    }
    const uint32_t dl = sbase + 18 * SLOT + 4 * 12288 + wid * 384;
#pragma unroll 1
    for (int slot = (wid == 12 ? 15 : wid > 12 ? 15 - wid : 14 - wid) * 4 + (kj ^ 3); slot < QUEUE; slot += 64) {
      uint2 rq;
#pragma unroll 1
      for (uint32_t spin = 0;; spin++) {
        uint32_t done[2];
        ld_pair(&rq.x, tm.scr->req + slot);
        if (slot < EARLY) {
          ld_pair(done, tm.scr->mail[56] + MAXEX);
          if (rq.y || (done[1] == epoch && slot >= done[0])) break;
        } else {
          asm volatile("ld.acquire.gpu.global.u32 %0, [%1];\n" : "=r"(done[1]) : "l"(tm.scr->ready + 6) : "memory");
          if (rq.y) break;
          if (done[1] == epoch) {
            asm volatile("ld.relaxed.gpu.global.u32 %0, [%1];\n" : "=r"(done[0]) : "l"(tm.scr->ready + 8 + ((epoch >> 7) & 1)) : "memory");
            if (slot - EARLY >= done[0]) break;
          }
        }
        if (spin > (1u << 22)) __trap();
        __nanosleep(100);
      }
      if (!rq.y) continue;
      __syncwarp();
      if (lane == 0) tm.scr->req[slot] = make_uint2(0, 0);
      const int tap = rq.y & 15, ki = (tap * 11) >> 5, gy = (int)bf16lo(rq.x), gx = (int)bf16hi(rq.x);
      const int cy = min(max((int)((rq.y >> 12) & 255) + ki - 1, 0), IH - 1), cx = min(max((int)((rq.y >> 4) & 255) + tap - ki * 3 - 1, 0), IW - 1);
      if (lane < 24) {
        const uint2* pc = reinterpret_cast<const uint2*>(x) + lane;
        const int p = (gy * IW + gx) * 24, sx = gx < IW - 1 ? 24 : 0, sy = gy < IH - 1 ? IW * 24 : 0;
        const uint2 v0 = __ldg(pc + p), v1 = __ldg(pc + p + sx), v2 = __ldg(pc + p + sy), v3 = __ldg(pc + p + sy + sx);
        const uint2 c = __ldg(pc + (cy * IW + cx) * 24);
        uint32_t q0, q1;
        coefs(frac2(rq.x), q0, q1);
        const uint32_t d0 = hsub2(blend(q0, q1, v0.x, v1.x, v2.x, v3.x), c.x), d1 = hsub2(blend(q0, q1, v0.y, v1.y, v2.y, v3.y), c.y);
        const uint32_t dd[4] = {__byte_perm(d0, 0, 0x1010), __byte_perm(d0, 0, 0x3232), __byte_perm(d1, 0, 0x1010), __byte_perm(d1, 0, 0x3232)};
        sts128(dl + lane * 16, dd);
      }
      __syncwarp();
      mbar_wait(bars + 4 * 8);
      float sum[8] = {};
      const int l24 = min(lane, 23);
#pragma unroll 1
      for (int b = 0; b < 6; b++) {
        uint32_t part[4] = {};
#pragma unroll
        for (int i = 0; i < 8; i++) {
          uint32_t wv[4];
          lds128(wv, sbase + (b >> 1) * 6 * SLOT + tap * 6144 + (b & 1) * 3072 + i * 384 + l24 * 16);
          const uint32_t d = lds32(dl + (b * 16 + i * 2 + (l24 >= 12)) * 4);
#pragma unroll
          for (int k = 0; k < 4; k++) part[k] = hfma2(d, wv[k], part[k]);
        }
#pragma unroll
        for (int k = 0; k < 4; k++) {
          sum[k * 2] += bf16lo(part[k]);
          sum[k * 2 + 1] += bf16hi(part[k]);
        }
      }
#pragma unroll
      for (int k = 0; k < 8; k++) sum[k] += __shfl_down_sync(0xffffffffu, sum[k], 12);
      if (lane < 12) {
#pragma unroll
        for (int k = 0; k < 4; k++)
          st_pair(tm.scr->res[slot] + lane * 4 + k, pack2(sum[k * 2], sum[k * 2 + 1]), epoch);
      }
      TSE(1);
    }
    mbar_wait(bars + 4 * 8);
  } else if (wid < 8) {
    const int wg = wid >> 2, warp = wid & 3;
    if (cta < 48) {
    const int f = wid * 4 + (lane >> 3), g = g0 + (lane & 7);
    uint32_t cf[36];
    wait_until(tstart, BSLEEP);
    {
      const uint32_t* op = offs + (band ? g * IW + f : f * IW + g) * 9;
#pragma unroll
      for (int a = 0; a < 3; a++)
#pragma unroll
        for (int b = 0; b < 3; b++) cf[a * 3 + b] = __ldg(op + (band ? b * 3 + a : a * 3 + b));
    }
    asm volatile("bar.sync 0, 512;\n" ::: "memory");
    {
      const uint32_t base = pack2((float)f, (float)g), sel = band ? 0x1032u : 0x3210u;
      const uint32_t tab = sbase + SM_YT + wid * 1152;
      uint32_t bad = 0;
#pragma unroll
      for (int a = 0; a < 3; a++)
#pragma unroll
        for (int b = 0; b < 3; b++) {
          const uint32_t gp = hadd2(base, tap_delta(a, b));
          const uint32_t pos = clip2(hadd2(gp, __byte_perm(cf[a * 3 + b], 0, sel)));
          uint32_t d = hsub2(pos, hmin2(gp, 0x435f435fu));
          if ((d & 0x7fff7fffu) > 0x3f80u) {
            bad = 1;
            d = a == 0 && f == 0 ? 0x3f80u : 0u;
          }
          sts32(tab + (lane & 7) * 144 + (b * 12 + (lane >> 3) * 3 + a) * 4, (d << 16) | (d & 0x8000u ? 0x3210u : 0x7654u));
        }
      if (bad && g >= 34) sts32(bars + O_CNT, FAILED);
      __syncwarp();
      arrive_if(lane == 0 ? bars + B_OS * 8 : 0u);
      asm volatile("setmaxnreg.inc.sync.aligned.u32 224;\n");
      __syncwarp();
#pragma unroll
      for (int i = 0; i < 9; i++) lds128(cf + i * 4, tab + (lane >> 2) * 144 + i * 16);
    }
    uint32_t xa[3];
#pragma unroll
    for (int b = 0; b < 3; b++)
      xa[b] = swz(sbase + SM_YX + ((wid * 4 + (lane >> 4)) * 10 + min((lane & 7) + b, IW - g0)) * 64, (lane >> 3) & 1);
    float acc[2][48];
    uint32_t X[2][16], A[2][12];
    auto fetch = [&](uint32_t* r, uint32_t a) {
#pragma unroll
      for (int i = 0; i < 4; i++) ldsm4(r + i * 4, (a ^ ((i & 1) * 32)) + i * 1280);
    };
    uint64_t bd = w_desc(sbase);
    uint32_t wf = bars + B_WF * 8;
    mbar_wait(bars + B_XF * 8);
    TSE(0);
    fetch(X[0], xa[0]);
    mbar_wait(wf);
#pragma unroll 1
    for (int s = 0; s < 3; s++) {
#pragma unroll
      for (int n = 0; n < 6; n++) {
        const int b = n >> 1;
        if (n == 5) {
          mbar_wait(bars + (B_XF + min(s + 1, 2)) * 8);
#pragma unroll
          for (int k = 0; k < 3; k++) xa[k] += s < 2 ? YSLICE : 0;
        }
        fetch(X[~n & 1], xa[(n + 1) % 6 >> 1] ^ ((~n & 1) * 32));
        const uint32_t* xr = X[n & 1];
        uint32_t D[7][2];
#pragma unroll
        for (int j = 0; j < 7; j++)
#pragma unroll
          for (int e = 0; e < 2; e++) D[j][e] = hsub2(xr[(j + 1) * 2 + e], xr[j * 2 + e]);
#pragma unroll
        for (int t = 0; t < 2; t++) {
          wgmma_wait<1>();
#pragma unroll
          for (int a = 0; a < 3; a++)
#pragma unroll
            for (int i = 0; i < 4; i++) {
              const int o = t * 2 + (i & 1), e = i >> 1, j = o + a + 1;
              const uint32_t c = cf[b * 12 + o * 3 + a];
              A[t][a * 4 + i] = hfma2_hi(c, prmt(D[j - 1][e], D[j][e], c), xr[j * 2 + e]);
            }
          wgmma_fence();
#pragma unroll
          for (int a = 0; a < 3; a++) wgmma_rs(acc[t], A[t] + a * 4, bd + n * (SLOT >> 4) + a * 192, (n | a) ? 1 : s);
          wgmma_commit();
        }
        if (n & 1) mbar_wait(wf + (b + 1) * 8);
        if (n == 1 && s == 1 && elect_one()) arrive_if(bars + B_WE * 8);
      }
      bd += 6 * SLOT >> 4;
      wf += 24;
    }
    TSE(1);
    const int lane = thread_id() & 31;
    const uint32_t stg = sbase + wg * 3 * SLOT + (wid & 3) * 2048 + (lane & 15) * 64 + ((((lane >> 4) ^ (lane >> 1)) & 3) << 4);
    wgmma_wait<1>();
    acc_fence(acc[0]);
#pragma unroll
    for (int jp = 0; jp < 6; jp++) stage16<8192>(acc[0], jp, stg);
    wgmma_wait<0>();
    acc_fence(acc[1]);
#pragma unroll
    for (int jp = 0; jp < 6; jp++) stage16<8192>(acc[1], jp, stg + 1024);
    proxy_fence();
    __syncwarp();
    arrive_if(lane == 0 ? bars + (B_ST + wg * 4) * 8 : 0u);
    } else if (cta < NI) {
      asm volatile("bar.sync 0, 512;\n" ::: "memory");
      asm volatile("setmaxnreg.inc.sync.aligned.u32 224;\n");
    } else {
    {
      uint32_t g[3][3][4], src[3], dst[3];
#pragma unroll
      for (int r = 0; r < 3; r++) {
        src[r] = sbase + u_src(tid + r * 384);
        dst[r] = sbase + u_dst(tid + r * 384);
      }
      asm volatile("bar.sync 0, 512;\n" ::: "memory");
      mbar_wait(bars + (B_WF + 1) * 8);
#pragma unroll
      for (int r = 0; r < 3; r++) {
#pragma unroll
        for (int k = 0; k < 3; k++) lds128(g[r][k], src[r] + k * 2 * SLOT);
      }
#pragma unroll
      for (int r = 0; r < 3; r++) u_math16(g[r], dst[r]);
      proxy_fence();
      __syncwarp();
      arrive_if(lane == 0 ? bars + B_WF * 8 : 0u);
    }
    asm volatile("setmaxnreg.inc.sync.aligned.u32 224;\n");
    float m[4][48];
    const uint32_t vb = sbase + SM_V + wg * UNIT;
    const uint64_t bd0 = w_desc(sbase + SM_W), ad12 = a_desc(vb + 2 * PLANE), ad05 = a_desc(vb + (wg ? 4 * PLANE : 0));

    const uint64_t d34 = wg ? -(2 * PLANE >> 4) : 2 * PLANE >> 4;
    uint64_t ad = ad12;
    uint32_t wf = bars + B_WF * 8, a[4];
    {
      const int t = thread_id();
#pragma unroll
      for (int j = 0; j < 4; j++) a[j] = swz(vb + j * PLANE + ((t & 127) >> 3) * 64, t >> 1) + (t & 1) * 8;
    }
#pragma unroll 1
    for (int sl = 0; sl < 3; sl++) {
      {
        uint32_t d[6][2], d2[6][2], tq[4];
        const uint32_t a5 = y0 == 216 && ((wg ^ ry) & 1) ? a[0] : a[1], o34 = wg ? 0 : 4 * PLANE;
        TQ(0);
        mbar_wait(bars + (B_XF + sl * 2 + wg) * 8);
        TQ(1);
        if (CG != 2 && (CG ? wg | sl : sl)) mbar_wait(bars + (B_XR + sl * 2 + wg - 1) * 8);
        if (((SH >> ((sl * 2 + wg) * 4)) & 3) == 1) {
          v_load(d, a, a5, 1024);
          v_store(d, a, 4 * PLANE - o34, o34, 1024);
        }
        v_load(d, a, a5, 2048);
        if (CPF) v_load(d2, a, a5, 3072);
        v_store(d, a, 4 * PLANE - o34, o34, 2048);
        if (!CPF) v_load(d2, a, a5, 3072);
        v_store(d2, a, 4 * PLANE - o34, o34, 3072);
        proxy_fence();
        __syncwarp();
        if (elect_one()) arrive_if(bars + (B_XR + sl * 2 + wg) * 8);
#pragma unroll
        for (int j = 0; j < 4; j++) asm volatile("add.u32 %0, %0, %1;\n" : "+r"(a[j]) : "n"(2 * UNIT));
        TQ(2);
        mbar_wait(wf);
        TQ(3);
        mbar_wait(bars + (B_XR + sl * 2 + wg) * 8);
        if (LOCK && wg && sl == 2) asm volatile("bar.sync 6, 256;\n" ::: "memory");
      }
#pragma unroll
      for (int n = 0; n < 8; n++) {
        const int k = n & 3;
        wgmma_fence();
#pragma unroll
        for (int kj = 0; kj < 3; kj++)
          wgmma_ss(m[k], (k < 2 ? ad : ad + d34) + (k & 1) * (PLANE >> 4) + n / 4 * 2 + kj * 4, bd0 + n * (SLOT >> 4) + kj * 192, (n / 4 | kj) ? 1 : sl);
        wgmma_commit();
        if (n < 7) {
          if (sl) mbar_wait(wf + (n + 1) * 8);
          wgmma_wait<1>();
          if (warp == 0 && n) asm volatile("bar.arrive %0, 96;\n" ::"r"(7 + n) : "memory");
          if ((BUB >> n) & 1) wgmma_wait<0>();
        }
      }
      if (sl == 2 && (LOCK || wg)) asm volatile("bar.arrive %0, 256;\n" ::"r"(wg ? 4 : 6) : "memory");
      wgmma_wait<1>();
      if (warp == 0) asm volatile("bar.arrive 14, 96;\n" ::: "memory");
      wgmma_wait<0>();
      if (warp == 0) asm volatile("bar.arrive 15, 96;\n" ::: "memory");
      ad += 2 * UNIT >> 4;
      wf += 64;

    }
    const int lane = thread_id() & 31;
    const uint32_t stg = sbase + SM_X + 2 * UNIT + wg * 21504 + warp * 1024 + (lane & 15) * 64 + ((((lane >> 4) ^ (lane >> 1)) & 3) << 4);
    const uint32_t stb = lane == 0 ? bars + (B_ST + wg * 4) * 8 : 0u;
    auto publish = [&](int k) {
      proxy_fence();
      __syncwarp();
      arrive_if(stb ? stb + k * 8 : 0u);
    };
#pragma unroll
    for (int k = 0; k < 4; k++) acc_fence(m[k]);
    float dep = 0.f;
#pragma unroll
    for (int i0 = 0; i0 < 48; i0 += TG) {
      const float k0 = __uint_as_float((__float_as_uint(dep) & never) | 0xbf088889u);
      const float k1 = __uint_as_float((__float_as_uint(dep) & never) | 0xbf800000u);
#pragma unroll
      for (int i = i0; i < i0 + TG; i++) {
        m[0][i] *= k0;
        m[3][i] = fmaf(k1, m[3][i], m[2][i]);
        m[1][i] = fmaf(-8.0f / 15.0f, m[1][i], m[0][i]);
        m[2][i] = fmaf(-0.5f, m[3][i], m[2][i]);
        m[0][i] = fmaf(-0.5f, m[1][i], m[0][i]);
        m[1][i] = fmaf(4.0f / 15.0f, m[2][i], m[1][i]);
        m[0][i] = fmaf(4.0f / 15.0f, m[3][i], m[0][i]);
        m[2][i] = fmaf(0.25f, m[1][i], m[2][i]);
        m[3][i] = fmaf(0.25f, m[0][i], m[3][i]);
        dep = m[0][i];
        if ((i & 7) == 7) {
          stage16<4096>(m[2], i >> 3, stg);
          stage16<4096>(m[0], i >> 3, stg + 2 * UNIT);
        }
      }
    }
    publish(0);
    asm volatile("bar.sync %0, 256;\n" ::"r"(4 + wg) : "memory");
    const uint64_t bdx = w_desc(sbase + SM_X);
    const uint32_t s05 = vb + (wg ? 4 * PLANE : 0) + warp * 1024 + (lane & 15) * 64;
#pragma unroll
    for (int j = 0; j < 12; j++) {
      float* acc = j < 6 ? m[1] : m[3];
      const int c = j % 6;
      const uint64_t ad = ad05 + (c >> 1) * (2 * UNIT >> 4) + (c & 1) * 2 + (j < 6 ? 0 : PLANE >> 4);
      const uint64_t bd = j < 3 ? bdx + j * (SLOT >> 4) : j == 3 ? bdx + ((2 * UNIT + 12288) >> 4) : bd0 + (j - 4) * (SLOT >> 4);
      if (j != 1 && j != 2) mbar_wait(bars + (B_WF + 24 + j) * 8);
      wgmma_fence();
#pragma unroll
      for (int kj = 0; kj < 3; kj++) wgmma_ss(acc, ad + kj * 4, bd + kj * 192);
      wgmma_commit();
      if (j == 7) {
        wgmma_wait<2>();
        acc_fence(m[1]);
      }
      if (j >= 7 && j <= 9) {
#pragma unroll
        for (int jp = j * 2 - 14; jp < j * 2 - 12; jp++) stage16<2 * UNIT>(m[1], jp, swz(s05, lane >> 4));
      }
      if (j == PUB1) publish(1);
      if (HAND == j && !wg) asm volatile("bar.arrive 5, 256;\n" ::: "memory");
    }
    wgmma_wait<0>();
    acc_fence(m[3]);
    TSE(1);
#pragma unroll
    for (int jp = 0; jp < 6; jp++) stage16<2 * UNIT>(m[3], jp, swz(s05 + PLANE, lane >> 4));
    if (HAND == 12 && !wg) asm volatile("bar.arrive 5, 256;\n" ::: "memory");
    publish(2);
    }
    int rounds = 1;
    const int tid = thread_id(), lane = tid & 31;
    if (cta < 48 || cta >= NI) {
      mbar_wait(bars + B_OK * 8);
      rounds = lds32(bars + O_VER) != FAILED ? 0 : cta < 48 ? 2 : 4;
      rounds = __shfl_sync(0xffffffffu, rounds, 0);
    }
    if (rounds) {
      const bool lead = warp == 0 && elect_one();
      if (rounds > 1) {
        if (tid == 0) {
#pragma unroll
          for (int i = 0; i < 15; i++) mbar_init(bars + (B_G + i) * 8, 1);
          asm volatile("fence.mbarrier_init.release.cluster;\n" ::: "memory");
        }
        proxy_fence();
        asm volatile("bar.sync 3, 256;\n" ::: "memory");
      }
      const uint32_t win = sbase + SM_GX + wg * 3 * GSLICE, gxb = bars + (B_G + 9 + wg * 3) * 8;
      const uint64_t bd0 = w_desc(sbase);
      float acc[48];
#pragma unroll 1
      for (int r = 0; r < rounds; r++) {
        int ty, tx, bx;
        asm volatile("mov.u32 %0, %%ctaid.x;\n" : "=r"(bx));
        const int cta = role_of(bx), ry = (cta - NI) / 3, x0 = 32 + (cta - NI - ry * 3) * 64, y0 = 32 + ry * 8;
        const int band = cta >= 24, g0 = 32 + (cta - band * 24) * 8;
        if (cta >= NI) { ty = y0; tx = x0 + r * 16 + wg * 8; }
        else if (cta < 48) { ty = band ? g0 : r * 16 + wg * 8; tx = band ? r * 16 + wg * 8 : g0; }
        else { ty = (cta & 1) * 8 + wg * 16; tx = (cta & 2) * 4 + ((cta >> 2 ^ wg) & 1) * 16; }
        if (lead && rounds > 1) {
#pragma unroll 1
          for (int sl = 0; sl < 3; sl++) {
            mbar_expect_tx(gxb + sl * 8, GSLICE);
            tma_load_3d(win + sl * GSLICE, &tm.gx, gxb + sl * 8, sl * 32, tx - 2, ty - 2);
            if (r == 0) {
#pragma unroll 1
              for (int ki = 0; ki < 3; ki++) {
                if (!wg) mbar_expect_tx(bars + (B_G + sl * 3 + ki) * 8, 2 * SLOT);
                tma_load_5d(sbase + ((sl * 3 + ki) * 2 + wg) * SLOT, &tm.bw[1], bars + (B_G + sl * 3 + ki) * 8, sl * 32 + wg * 16, 0, ki);
              }
            }
          }
        }
        const int ph = ty + warp * 2 + ((lane >> 3) & 1), pw = tx + (lane & 7);
        const uint32_t* op = offs + (ph * IW + pw) * 9;
        const uint32_t base = pack2((float)ph, (float)pw);
        uint32_t ent[9], cf[36], need = 0, out = 0;
#pragma unroll
        for (int m = 0; m < 9; m++) ent[m] = __ldg(op + m);
#pragma unroll
        for (int m = 0; m < 9; m++) {
          const uint32_t pos = clip2(hadd2(hadd2(base, tap_delta(m / 3, m % 3)), ent[m])), fr = frac2(pos);
          const uint32_t iy = (int)bf16lo(pos) - (ty - 2), ix = (int)bf16hi(pos) - (tx - 2);
          out |= max(iy, ix) > 10;
          need |= ((fr >> 16 ? 1u : 0u) | (fr & 0xffffu ? 2u : 0u) | (fr >> 16 && (fr & 0xffffu) ? 4u : 0u)) << (m * 3);
          const uint32_t up = (fr & 0xffffu) >= 0x3f00u, fn = hmin2(fr, hsub2(0x3f803f80u, fr));
          const uint32_t pp = ((iy + up) * 12 + ix) * 0x10001u + (fr >= 0x3f000000u ? 1u : 0x10000u);
          ent[m] = ((pp * 64 + ((pp << 3) & 0x300030u)) ^ ((lane >> 4) * 0x100010u)) | up;
          coefs(__shfl_sync(0xffffffffu, fn, lane >> 2), cf[m * 4], cf[m * 4 + 1]);
          coefs(__shfl_sync(0xffffffffu, fn, (lane >> 2) + 8), cf[m * 4 + 2], cf[m * 4 + 3]);
        }
        need = __reduce_or_sync(0xffffffffu, need);
        asm volatile("{\n.reg .pred p;\nsetp.ne.u32 p, %0, 0;\nbarrier.red.popc.u32 %0, %1, 128, p;\n}\n" : "+r"(out) : "r"(1 + wg) : "memory");
        out = __shfl_sync(0xffffffffu, out, 0);
        TSE(0);
        if (!out) {
          uint32_t C[2][4][8], A[2][8];
#pragma unroll
          for (int i = 0; i < 64; i++) C[0][0][i] = 0;
          auto fetch = [&](uint32_t (*c)[8], int m, uint32_t slice) {
            const uint32_t a0 = (ent[m] & 0xfff0u) + slice, a1 = (ent[m] >> 16) + slice, dy = 768 - (ent[m] & 1) * 1536;
#pragma unroll
            for (int h = 0; h < 2; h++) {
              ldsm4(c[0] + h * 4, a0 ^ (h * 32));
              ldsm4_if(c[1] + h * 4, a1 ^ (h * 32), need & (1 << (m * 3)));
              ldsm4_if(c[2] + h * 4, (a0 ^ (h * 32) ^ 32) + dy, need & (2 << (m * 3)));
              ldsm4_if(c[3] + h * 4, (a1 ^ (h * 32) ^ 32) + dy, need & (4 << (m * 3)));
            }
          };
#pragma unroll 1
          for (int sl = 0; sl < 3; sl++) {
            const uint32_t slice = win + sl * GSLICE;
            const uint64_t bd = bd0 + sl * (6 * SLOT >> 4);
            mbar_wait(gxb + sl * 8, r & 1);
            fetch(C[0], 0, slice);
#pragma unroll
            for (int m = 0; m < 9; m++) {
              if (m < 8) fetch(C[~m & 1], m + 1, slice);
              if (m % 3 == 0) mbar_wait(bars + (B_G + sl * 3 + m / 3) * 8);
              if (m >= 2) wgmma_wait<1>();
#pragma unroll
              for (int i = 0; i < 8; i++)
                A[m & 1][i] = blend(cf[m * 4 + (i & 1) * 2], cf[m * 4 + (i & 1) * 2 + 1], C[m & 1][0][i], C[m & 1][1][i], C[m & 1][2][i], C[m & 1][3][i]);
              wgmma_fence();
              wgmma_rs(acc, A[m & 1], bd + m / 3 * (2 * SLOT >> 4) + m % 3 * 192, m ? 1 : sl);
              wgmma_rs(acc, A[m & 1] + 4, bd + (m / 3 * 2 + 1) * (SLOT >> 4) + m % 3 * 192);
              wgmma_commit();
            }
            wgmma_wait<0>();
          }
        } else {
#pragma unroll 1
          for (int i = 0; i < 12; i++) mbar_wait(i < 9 ? bars + (B_G + i) * 8 : gxb + (i - 9) * 8, i < 9 ? 0 : r & 1);
          const uint32_t scratch = win + warp * 3072 + lane * 16;
#pragma unroll 1
          for (int m = 0; m < 9; m++) {
            const int ki = (m * 11) >> 5;
            const uint32_t pos = clip2(hadd2(pack2((float)(ph + ki - 1), (float)(pw + m - ki * 3 - 1)), __ldg(op + m)));
            const int gy = (int)bf16lo(pos), gx = (int)bf16hi(pos), sx = gx < IW - 1 ? 12 : 0, sy = gy < IH - 1 ? IW * 12 : 0;
            const uint4* pc = x + (gy * IW + gx) * 12 + (lane >> 4);
            uint32_t q0, q1, V[6][4][4], A[6][4];
            coefs(frac2(pos), q0, q1);
#pragma unroll
            for (int k = 0; k < 6; k++)
#pragma unroll
              for (int c = 0; c < 4; c++) ldg128(V[k][c], pc + k * 2 + (c & 1) * sx + (c >> 1) * sy);
#pragma unroll
            for (int k = 0; k < 6; k++) {
#pragma unroll
              for (int i = 0; i < 4; i++) V[k][0][i] = blend(q0, q1, V[k][0][i], V[k][1][i], V[k][2][i], V[k][3][i]);
              sts128(scratch + k * 512, V[k][0]);
            }
            __syncwarp();
#pragma unroll
            for (int k = 0; k < 6; k++) ldsm4(A[k], scratch + k * 512);
            wgmma_fence();
#pragma unroll
            for (int k = 0; k < 6; k++) wgmma_rs(acc, A[k], bd0 + ((k >> 1) * 6 + ki * 2 + (k & 1)) * (SLOT >> 4) + (m - ki * 3) * 192, k ? 1 : m);
            wgmma_commit();
            wgmma_wait<0>();
          }
        }
        acc_fence(acc);
        TSE(1);
        asm volatile("bar.sync %0, 128;\n" ::"r"(1 + wg) : "memory");
#pragma unroll
        for (int jp = 0; jp < 6; jp++) stage16<4096>(acc, jp, win + warp * 1024 + (lane & 15) * 64 + ((((lane >> 4) ^ (lane >> 1)) & 3) << 4));
        proxy_fence();
        asm volatile("bar.sync %0, 128;\n" ::"r"(1 + wg) : "memory");
        if (lead) {
          tma_store(&tm.gout, win, tx, ty);
          asm volatile("cp.async.bulk.commit_group;\ncp.async.bulk.wait_group.read 0;\n" ::: "memory");
          TSE(2);
        }
      }
    }
  } else if (wid < 12) {
    asm volatile("setmaxnreg.dec.sync.aligned.u32 32;\n");
    const int tid = thread_id(), lane = tid & 31;

    const bool one = elect_one();
    if (one && cta < NI) {
#pragma unroll
      for (int i = 0; i < 4; i++) mbar_init(bars + (B_G + (wid - 8) * 4 + i) * 8, 1);
      asm volatile("fence.mbarrier_init.release.cluster;\n" ::: "memory");
    }
    if (one && cta >= NI) {
#pragma unroll
      for (int i = 0; i < 7; i++) mbar_init(bars + (B_WF + 8 + (wid - 8) * 7 + i) * 8, 1);
      if (wid == 8) mbar_init(bars + B_WF * 8, 12);
      mbar_init(bars + (B_UR + wid - 8) * 8, 1);
      asm volatile("fence.mbarrier_init.release.cluster;\n" ::: "memory");
    }
    asm volatile("bar.arrive 3, 256;\n" ::: "memory");
    asm volatile("bar.sync 0, 512;\n" ::: "memory");
    if (cta >= NI) {
      mbar_wait(bars + (B_WF + 1) * 8);
#pragma unroll 1
      for (int t = tid; t < 1152; t += 384) {
        uint32_t g[3][4];
        const uint32_t src = sbase + u_src(t);
#pragma unroll
        for (int k = 0; k < 3; k++) lds128(g[k], src + k * 2 * SLOT);
        u_math16(g, sbase + u_dst(t));
      }
      proxy_fence();
      __syncwarp();
      arrive_if(one ? bars + B_WF * 8 : 0u);
      uint32_t a[4], d[1][6][2];
#pragma unroll
      for (int j = 0; j < 4; j++) a[j] = swz(sbase + SM_V + j * PLANE + ((tid & 127) >> 3) * 64, lane >> 1) + (lane & 1) * 8;
      const bool bot = y0 == 216;
      uint32_t off = 0;
#pragma unroll 1
      for (int u = 0; u < 6; u++) {
        const uint32_t a5 = bot && ((u ^ ry) & 1) ? a[0] : a[1], o34 = u & 1 ? 0 : 4 * PLANE;
        mbar_wait(bars + (B_XF + u) * 8);
#pragma unroll 1
        for (int i = 0; i < ((u & 3) == (wid & 3) ? 3 : 2); i += i ? 1 : 3 - ((SH >> (u * 4)) & 3)) {
          const uint32_t h = off + (i < 2 ? i * 1024 : 4096 - (wid & 2) * 256);
          v_load(d[0], a, a5, i == 2 && (lane & 16 || (x0 == 160 && lane >= 8)) ? h - (lane >> 3) * 64 : h);
          v_store(d[0], a, 4 * PLANE - o34, o34, h, i == 2 && lane >= 16 ? -1 : 0);
        }
        proxy_fence();
        __syncwarp();
        arrive_if(one ? bars + (B_XR + u) * 8 : 0u);
        off += UNIT + ((u ^ wid) & 1 ? -256 : 256);
      }
    }
  } else {
    asm volatile("setmaxnreg.dec.sync.aligned.u32 32;\n");
    const int tid = thread_id(), lane = tid & 31;
    const bool one = elect_one();
    if (wid != 12) {
      if (one) {
        if (cta >= NI) {
          if (wid == 13) {
#pragma unroll
            for (int i = 0; i < 6; i++) mbar_init(bars + (B_XR + i) * 8, 8);
          } else if (wid == 15) {
#pragma unroll
            for (int i = 2; i < 6; i++) mbar_init(bars + (B_XF + i) * 8, 1);
          }
        } else {
#pragma unroll
          for (int i = 0; i < 3; i++) mbar_init(bars + (B_WF + 1 + (wid - 13) * 3 + i) * 8, 1);
          if (wid < 15) mbar_init(bars + (wid == 13 ? B_WE : B_WF) * 8, wid == 13 ? 8 : 1);
          mbar_init(bars + (B_XF + wid - 13) * 8, 1);
        }
        if (wid == 14) {
#pragma unroll
          for (int i = 0; i < 8; i++) mbar_init(bars + (B_ST + i) * 8, 4);
#pragma unroll
          for (int i = B_OF; i <= B_OK; i++) mbar_init(bars + i * 8, i != B_OS ? 1 : cta < NI ? 8 : 2);
          sts32(bars + O_CNT, 0);
        }
        asm volatile("fence.mbarrier_init.release.cluster;\n" ::: "memory");
      }
      asm volatile("bar.arrive 3, 256;\n" ::: "memory");
      asm volatile("bar.sync 0, 512;\n" ::: "memory");
      if (cta >= 48 && cta < NI) {
        if (wid == 15 && one) asm volatile("red.relaxed.gpu.global.add.u32 [%0], 1;\n" ::"l"(tm.scr->ready + 6) : "memory");
      } else {
        uint32_t epoch = 0;
        if (cta >= NI && wid < 15) {
          const uint32_t lim = (pack2((float)max(y0, 34) - 1.5f, (float)max(x0, 34) - 1.5f) & 0x7f807f80u) - 0x04000400u;
          uint32_t big = 0;
          mbar_wait(bars + B_OF * 8);
#pragma unroll 1
          for (int i0 = 0; i0 < 18; i0 += 6) {
            uint32_t v[6][4];
#pragma unroll
            for (int i = 0; i < 6; i++) lds128(v[i], sbase + SM_OFF + (tid - 416) * 16 + (i0 + i) * 1024);
            __nv_bfloat162 mx = as_bf2(0u), mn = as_bf2(0u);
#pragma unroll
            for (int i = 0; i < 6 * 2; i++) {
              mx = __hmax2_nan(__hmax2_nan(mx, as_bf2(v[i >> 1][(i & 1) * 2])), as_bf2(v[i >> 1][(i & 1) * 2 + 1]));
              mn = __hmin2_nan(__hmin2_nan(mn, as_bf2(v[i >> 1][(i & 1) * 2])), as_bf2(v[i >> 1][(i & 1) * 2 + 1]));
            }
            big |= __hblt2(__hmax2_nan(mx, __hneg2(mn)), as_bf2(lim)) ? 0u : 1u << i0;
          }
          __syncwarp();
          arrive_if(one ? bars + B_OS * 8 : 0u);
          if (wid == 13) {
            mbar_wait(bars + B_OS * 8);
            mbar_wait(bars + (B_WF + X5W) * 8);
            if (one) {
              mbar_expect_tx(bars + (B_XF + 5) * 8, UNIT);
              tma_load_3d(sbase + SM_V + 5 * UNIT, &tm.x, bars + (B_XF + 5) * 8, 64, x0 - 1, y0 + (~ry & 1) * 4 - 1);
            }
          }
#pragma unroll 1
          for (uint32_t who; (who = __ballot_sync(0xffffffffu, big)) != 0;) {
            const int src = __ffs(who) - 1;
            const uint32_t b = __reduce_or_sync(0xffffffffu, lane == src ? big : 0u);
            if (lane == src) big &= big - 1;
            const uint32_t wi = ((wid - 13) * 32 + src + (__ffs(b) - 1 + (lane >> 2)) * 64) * 4 + (lane & 3), id = (wi * 7282) >> 16, tap = wi - id * 9;
            const int ki = (tap * 11) >> 5, h = y0 + (id >> 6), w = x0 + (id & 63);
            mbar_wait(bars + B_EP * 8);
            epoch = lds32(bars + O_EPO);
            if (lds32(bars + O_CNT) > MAXEX) big = 0;
            if (lane < 24 && h >= 34 && w >= 34) {
              const uint32_t gp = pack2((float)(h + ki - 1), (float)(w + (int)tap - ki * 3 - 1));
              const uint32_t pos = clip2(hadd2(gp, __ldg(offs + (h * IW + w) * 9 + tap)));
              if (pos != hmin2(gp, 0x435f435fu)) {
                const uint32_t i = count_up(bars + O_CNT);
                if (i < MAXEX)
                  sts32(bars + O_LST + i * 4, id | (request(tm.scr, min(atomicAdd(tm.scr->ready + 8 + ((epoch >> 7) & 1), 1u) + EARLY, QUEUE), pos, h, w, tap) << 16));
              }
            }
            __syncwarp();
          }
          if (wid == 14) asm volatile("bar.arrive 7, 64;\n" ::: "memory");
        }
        if (wid == 13) {
          uint32_t m[2] = {}, cnt = 0;
          mbar_wait(bars + B_EP * 8);
          epoch = lds32(bars + O_EPO);
          if (cta >= NI ? x0 == 32 || y0 == 32 : g0 == 32) {
#pragma unroll 1
            for (uint32_t spin = 0;; spin++) {
              ld_pair(m, tm.scr->mail[cta] + min(lane, MAXEX));
              const uint32_t have = __ballot_sync(0xffffffffu, m[1] == epoch);
              cnt = __reduce_max_sync(0xffffffffu, lane == MAXEX ? m[0] : 0u);
              if ((have >> MAXEX) && (cnt > MAXEX || !(~have & ((1u << cnt) - 1)))) break;
              if (spin > (1u << 22)) __trap();
            }
          }
          if (cta >= NI) asm volatile("bar.sync 7, 64;\n" ::: "memory");
          else mbar_wait(bars + B_OS * 8);
          if (one) asm volatile("red.relaxed.gpu.global.add.u32 [%0], 1;\n" ::"l"(tm.scr->ready + 6) : "memory");
          const uint32_t own = lds32(bars + O_CNT);
          if (own && lane >= cnt) m[0] = lds32(bars + O_LST + ((lane - cnt) & 15) * 4);
          cnt += own;
          if (cnt > MAXEX || __any_sync(0xffffffffu, lane < cnt && m[0] >> 16 == QUEUE)) cnt = FAILED;
          const uint32_t id = lane < cnt ? m[0] & 511 : 512;
          const uint32_t rows = cnt == FAILED ? FAILED : __reduce_or_sync(0xffffffffu, lane < cnt ? 1u << (id >> (cta < NI ? 7 : 6)) : 0u);
          if (one) sts32(bars + O_VER, rows);
          __syncwarp();
          arrive_if(one ? bars + B_OK * 8 : 0u);
          TSE(0);
#pragma unroll 1
          for (uint32_t got = 0; got < cnt && cnt != FAILED; got += 4) {
            const uint32_t i = min(got + (lane >> 3), cnt - 1);
            const uint2* r = tm.scr->res[__shfl_sync(0xffffffffu, m[0], i) >> 16] + (lane & 7);
            uint32_t v[12];
#pragma unroll 1
            for (uint32_t spin = 0;; spin++) {
              uint32_t miss = 0;
#pragma unroll
              for (int k = 0; k < 6; k++) ld_pair(v + k * 2, r + k * 8);
#pragma unroll
              for (int k = 0; k < 6; k++) miss |= v[k * 2 + 1] ^ epoch;
              if (__all_sync(0xffffffffu, !miss)) break;
              if (spin > (1u << 22)) __trap();
            }
#pragma unroll
            for (int k = 0; k < 6; k++) sts32(bars + O_COR + i * 192 + (lane & 7) * 4 + k * 32, v[k * 2]);
          }
          __syncwarp();
#pragma unroll 1
          for (int i = cnt && cnt != FAILED ? -1 : 8; i < 8; i++) {
            const int t = (i >> 1) & 1, r = (i & 1) + ((i >> 1) & 2), row = cta < NI ? i : ((t ^ ry) & 1) * 4 + ((2 - r) & 3);
            if (i >= 0 && !((rows >> row) & 1)) continue;
            const uint32_t base = cta < NI ? sbase + (i & 1) * 3 * SLOT
                                           : r < 2 ? sbase + SM_X + (2 + r * 2) * UNIT + t * 21504 : sbase + SM_V + t * (UNIT + 4 * PLANE) + (r - 2) * PLANE;
            const uint32_t pitch = cta < NI ? 8192 : r < 2 ? 4096 : 2 * UNIT;
            patch(bars + (i < 0 ? B_OK : B_ST + (cta < NI ? i * 4 : t * 4 + max(r - 1, 0))) * 8, i < 0 ? lane ? 512 : 0 : id - (row << (cta < NI ? 7 : 6)),
                  cta < NI ? 128 : 64, base, pitch, bars, i < 0 ? 12 : lane);
            if (one && i >= 0) {
              if (cta < NI) {
                tma_store(&tm.bout[band], base, g0, i * 16);
              } else {
#pragma unroll
                for (int k = 0; k < 3; k++) tma_store3(&tm.out, base + k * pitch, k * 32, x0, y0 + row);
              }
            }
          }
          if (one) asm volatile("cp.async.bulk.commit_group;\ncp.async.bulk.wait_group.read 0;\n" ::: "memory");
          TSE(2);
        } else {
          if (wid == 15) {
            auto poll = [&]() {
              uint32_t v;
              asm volatile("ld.acquire.gpu.global.u32 %0, [%1];\n" : "=r"(v) : "l"(tm.scr->ready + min(lane, 6)) : "memory");
              return v;
            };
            const uint32_t epoch = (__reduce_max_sync(0xffffffffu, lane == 6 ? poll() : 0u) & ~127u) + 128;
            if (one) sts32(bars + O_EPO, epoch);
            arrive_if(one ? bars + B_EP * 8 : 0u);
            if (cta >= NI) {
              uint32_t seen = 0;
              wait_until(tstart, POLLT);
#pragma unroll 1
              for (uint32_t spin = 0; seen != 7; spin++) {
                const uint32_t now = __ballot_sync(0xffffffffu, poll() == epoch) & ~seen & 7;
                if (now) {
                  asm volatile("fence.proxy.async.global;\n" ::: "memory");
                  arrive_if((now >> lane) & 1 ? bars + (B_UR + lane) * 8 : 0u);
                  seen |= now;
                }
                if (spin > (1u << 22)) __trap();
              }
            }
          }
          asm volatile("prefetch.tensormap [%0];\n" ::"l"(reinterpret_cast<uint64_t>(cta < NI ? &tm.bout[band] : &tm.out)) : "memory");
          const int t = wid & 1;
          mbar_wait(bars + B_OK * 8);
          const int r0 = cta < NI ? t : ((t ^ ry) & 1) * 4;
          const uint32_t skip = __shfl_sync(0xffffffffu, lds32(bars + O_VER), 0) >> r0;
          if (cta < NI) {
            mbar_wait(bars + (B_ST + t * 4) * 8);
            if (one && !(skip & 1)) tma_store(&tm.bout[band], sbase + t * 3 * SLOT, g0, t * 16);
          } else {
#pragma unroll
            for (int r = 0; r < 4; r++) {
              const uint32_t base = r < 2 ? sbase + SM_X + (2 + r * 2) * UNIT + t * 21504 : sbase + SM_V + t * (UNIT + 4 * PLANE) + (r - 2) * PLANE;
              if (r != 1) mbar_wait(bars + (B_ST + t * 4 + max(r - 1, 0)) * 8);
              if (r == PDR) mbar_wait(bars + (B_UR + 3) * 8);
              if (!((skip >> ((2 - r) & 3)) & 1)) {
#pragma unroll
                for (int k = 0; k < 3; k++)
                  if (one) tma_store3(&tm.out, base + k * (r < 2 ? 4096 : 2 * UNIT), k * 32, x0, y0 + r0 + ((2 - r) & 3));
              }
            }
          }
          if (one) asm volatile("cp.async.bulk.commit_group;\ncp.async.bulk.wait_group.read 0;\n" ::: "memory");
          TSE(2);
        }
      }
    } else if (cta < NI) {
        auto load_x = [&](int s) {
          mbar_expect_tx(bars + (B_XF + s) * 8, YSLICE);
          tma_load_3d(sbase + SM_YX + s * YSLICE, &tm.bx[band], bars + (B_XF + s) * 8, s * 32, g0 - 1, -2);
        };
        auto load_w = [&](int p) {
          const int s = (p * 11) >> 5, b = p - s * 3;
          mbar_expect_tx(bars + (B_WF + p) * 8, 2 * SLOT);
#pragma unroll
          for (int h = 0; h < 2; h++)
            tma_load_5d(sbase + (p * 2 + h) * SLOT, &tm.bw[band], bars + (B_WF + p) * 8, s * 32 + h * 16, band ? 0 : b, band ? b : 0);
        };
        asm volatile("bar.arrive 0, 512;\n" ::: "memory");
        asm volatile("bar.sync 3, 256;\n" ::: "memory");
        if (one && cta >= 48) {
#pragma unroll 1
          for (int sl = 0; sl < 3; sl++) {
            wait_until(tstart, CSLEEP + sl * GDT);
#pragma unroll
            for (int wg = 0; wg < 2; wg++) {
              mbar_expect_tx(bars + (B_G + 9 + wg * 3 + sl) * 8, GSLICE);
              tma_load_3d(sbase + SM_GX + (wg * 3 + sl) * GSLICE, &tm.gx, bars + (B_G + 9 + wg * 3 + sl) * 8, sl * 32,
                          (cta & 2) * 4 + ((cta >> 2 ^ wg) & 1) * 16 - 2, (cta & 1) * 8 + wg * 16 - 2);
            }
#pragma unroll 1
            for (int i = 0; i < 6; i++) {
              if (!(i & 1)) mbar_expect_tx(bars + (B_G + sl * 3 + (i >> 1)) * 8, 2 * SLOT);
              tma_load_5d(sbase + (sl * 6 + i) * SLOT, &tm.bw[1], bars + (B_G + sl * 3 + (i >> 1)) * 8, sl * 32 + (i & 1) * 16, 0, i >> 1);
            }
          }
        }
        if (one && cta < 48) {
          arrive_if(bars + (B_WF + 9) * 8);
#pragma unroll 1
          for (int p = 0; p < 9; p++) {
            wait_until(tstart, p ? YWT + (p - 1) * YWDT : BSLEEP);
            if (p == 0 || p == 3 || p == 6) load_x(p >> 1 & 1 ? (p >> 2) + 1 : 0);
            if (p == 8) mbar_wait(bars + B_WE * 8);
            load_w(p);
          }
        }
    } else {
        auto load_x = [&](int u) {
          mbar_expect_tx(bars + (B_XF + u) * 8, UNIT);
          tma_load_3d(sbase + SM_V + u * UNIT, &tm.x, bars + (B_XF + u) * 8, (u >> 1) * 32, x0 - 1, y0 + ((u ^ ry) & 1) * 4 - 1);
        };
        asm volatile("bar.sync 3, 256;\n" ::: "memory");
        if (lane < 28) mbar_expect_tx(bars + (B_WF + 8 + lane) * 8, lane == 16 ? 3 * SLOT : lane == 17 || lane == 18 ? 0 : SLOT);
        if (smem_u32(smem) != sbase) __trap();
#pragma unroll 1
        for (int xu = 2; xu <= 3; xu++) {
          wait_until(tstart, XT1 + (xu - 1) * XDT);
          if (xu == 3) mbar_wait(bars + B_WF * 8);
          if (one) load_x(xu);
          if (xu == OFFAT && one) {
            mbar_expect_tx(bars + B_OF * 8, 2 * SLOT);
            tma_load_3d(sbase + SM_OFF, &tm.off, bars + B_OF * 8, 0, x0 * 9 / 32, y0);
          }
        }
        const uint4* src = tm.scr->u;
        uint32_t fb = bars + (B_WF + 8) * 8;
#pragma unroll 1
        for (int q = 0; q < 6; q++) {
          mbar_wait(bars + (B_UR + (q >> 1)) * 8);
          if (q == 4) {
            if (one) bulk_load<3 * SLOT>(sbase + SM_X, src, fb);
            if (one) bulk_load<SLOT>(sbase + SM_X + 2 * UNIT + 12288, src + 3 * 576, fb + 24);
            src += 4 * 576;
            fb += 32;
          }
          const uint32_t dst = sbase + SM_W + (q & 1) * 4 * SLOT, id = 8 + (q & 1) * 4;
#pragma unroll
          for (int k = 0; k < 4; k++) {
            asm volatile("bar.sync %0, 96;\n" ::"r"(id + k) : "memory");
            if (one) bulk_load<SLOT>(dst + k * SLOT, src + k * 576, fb + k * 8);
            if (k == 3 && q == 5 && one) arrive_if(bars + (B_UR + 3) * 8);
          }
          if (q == X4Q && one) load_x(4);
          src += 4 * 576;
          fb += 32;
        }
    }
  }
}

typedef CUresult (*EncodeTiledFn)(CUtensorMap*, CUtensorMapDataType, cuuint32_t, void*, const cuuint64_t*,
                                  const cuuint64_t*, const cuuint32_t*, const cuuint32_t*, CUtensorMapInterleave,
                                  CUtensorMapSwizzle, CUtensorMapL2promotion, CUtensorMapFloatOOBfill);

}

extern "C" void kernel_launch(void* const* d_in, const int* in_sizes, int n_in, void* d_out, int out_size) {
  static EncodeTiledFn encode = nullptr;
  static Scratch* scratch = nullptr;
  if (!encode) {
    void* fn = nullptr;
    cudaDriverEntryPointQueryResult qres;
    cudaGetDriverEntryPoint("cuTensorMapEncodeTiled", &fn, cudaEnableDefault, &qres);
    encode = (EncodeTiledFn)fn;
    cudaGetSymbolAddress((void**)&scratch, g_scratch);
    cudaFuncSetAttribute(dcn_kernel, cudaFuncAttributeMaxDynamicSharedMemorySize, SMEM_BYTES);
  }
  uint32_t* tsp = nullptr;
  Maps tm;
  tm.scr = scratch;
  auto make = [&](CUtensorMap* m, void* p, int rank, const cuuint64_t* dims, const cuuint64_t* strides, const cuuint32_t* box, bool swizzle) {
    const cuuint32_t es[5] = {1, 1, 1, 1, 1};
    encode(m, CU_TENSOR_MAP_DATA_TYPE_BFLOAT16, rank, p, dims, strides, box, es, CU_TENSOR_MAP_INTERLEAVE_NONE,
           swizzle ? CU_TENSOR_MAP_SWIZZLE_64B : CU_TENSOR_MAP_SWIZZLE_NONE, CU_TENSOR_MAP_L2_PROMOTION_NONE,
           CU_TENSOR_MAP_FLOAT_OOB_FILL_NONE);
  };
  const cuuint64_t PX = IC * 2, ROW = IW * IC * 2, TAP = IC * IC * 2;
  for (int t = 0; t < 2; t++) {
    const cuuint64_t dims[3] = {IC, IW, IH}, odims[4] = {32, IW, IH, 3}, strides[3] = {t ? ROW : PX, t ? PX : ROW, 64};
    const cuuint32_t xb[3] = {32, 66, 6}, ob[3] = {32, 64, 1}, bxb[3] = {32, 10, 36}, bob[4] = {32, 8, 16, 3};
    if (!t) make(&tm.x, d_in[0], 3, dims, strides, xb, true);
    if (!t) make(&tm.out, d_out, 3, dims, strides, ob, true);
    const cuuint32_t gxb[3] = {32, 12, 12}, gob[4] = {32, 8, 8, 3};
    if (!t) make(&tm.gx, d_in[0], 3, dims, strides, gxb, true);
    if (!t) make(&tm.gout, d_out, 4, odims, strides, gob, true);
    make(&tm.bx[t], d_in[0], 3, dims, strides, bxb, true);
    make(&tm.bout[t], d_out, 4, odims, strides, bob, true);
    const cuuint64_t wdims[5] = {32, IC, 3, 3, 3}, wstrides[4] = {PX, 64, TAP, 3 * TAP};
    const cuuint32_t wb[5] = {32, 16, 3, t ? 3u : 1u, t ? 1u : 3u};
    make(&tm.bw[t], d_in[2], 5, wdims, wstrides, wb, true);
  }
  {
    const cuuint64_t dims[3] = {64, 144, 9}, strides[2] = {128, TAP};
    const cuuint32_t box[3] = {64, 48, 9};
    make(&tm.w, d_in[2], 3, dims, strides, box, false);
    const cuuint64_t cdims[4] = {64, 144, 3, 3}, cstrides[3] = {128, TAP, 3 * TAP};
    const cuuint32_t cbox[4] = {64, 24, 1, 3};
    make(&tm.wc, d_in[2], 4, cdims, cstrides, cbox, false);
    const cuuint64_t odims[3] = {64, 63, IH}, ostrides[2] = {128, IW * 36};
    const cuuint32_t obox[3] = {64, 18, 8};
    make(&tm.off, d_in[1], 3, odims, ostrides, obox, false);
    const cuuint32_t cb[3] = {64, 1, IH};
    make(&tm.col, d_in[1], 3, odims, ostrides, cb, false);
  }
  dcn_kernel<<<GRID, NTHREADS, SMEM_BYTES>>>((const uint4*)d_in[0], (const uint32_t*)d_in[1], tsp, 0u, tm);
}
```

```cpp
#include <cuda_runtime.h>
#include <cuda.h>
#include <cuda_bf16.h>
#include <stdint.h>

namespace {

constexpr int IH = 224, IW = 224, IC = 96;
constexpr int GRID = 132, NTHREADS = 512;
constexpr int NI = 60;
constexpr int SLOT = 9216;
constexpr int SMEM_BYTES = 232448;
constexpr int PLANE = 66 * 64, UNIT = 6 * PLANE;
constexpr int SM_V = 256, SM_X = SM_V + 2 * PLANE, SM_W = 36 * PLANE + 512, SM_BAR = SM_W + 8 * SLOT;
constexpr int SM_RAW = SM_V + 3 * UNIT, SM_OFF = SM_V + 6 * UNIT - 2 * SLOT;
constexpr int YSLICE = 36 * 10 * 64, SM_YX = 16 * SLOT, SM_YT = SM_YX + 3 * YSLICE;
constexpr int GSLICE = 144 * 64, SM_GX = 18 * SLOT;
constexpr int B_WF = 0, B_WE = 36, B_XF = 60, B_XR = 66, B_ST = 72, B_UR = 80, B_OF = 84, B_OS = 85, B_EP = 86, B_OK = 87, B_G = 88, B_CR = 103;
constexpr int O_CNT = 832, O_VER = 848, O_EPO = 852, O_LST = 864, O_COR = 1024;
constexpr int MAXEX = 16, EARLY = 128, QUEUE = 192;
constexpr uint32_t FAILED = 0xffff;
#define PACE XT1 = 2500, XDT = 900, POLLT = 4600, YX0 = 1400, YWT = 3800, YWDT = 1100, GDT = 3500
constexpr uint32_t PACE;
#define YPS 1
#define YPN 1200
#define YWD2 800
#define EARLYW 1
#define FLIP 0
#define PFM 0
#define LOCK 1
#define PDR 1
#define PUB1 10
#define HAND 12
#define BUB 0
#define CPF 0
#define X5W 8
#define WAT 0
#define TG 8
#define OFFAT 3
#define X4Q 1

#define CSLEEP 800
#define X1T 1800
#define CG 2
#define SH 0x121212
#define BSLEEP 2000

struct Scratch {
  uint4 u[16 * SLOT / 16];
  uint4 w[12 * SLOT / 16];
  uint32_t ready[32];
  uint2 req[QUEUE];
  uint2 res[QUEUE][48];
  uint2 mail[GRID][32];
};
__device__ __align__(128) Scratch g_scratch;

#define TQ(i)
#define TSE(i)

__device__ __forceinline__ float bf16lo(uint32_t v) { return __uint_as_float(v << 16); }
__device__ __forceinline__ float bf16hi(uint32_t v) { return __uint_as_float(v & 0xffff0000u); }
__device__ __forceinline__ uint32_t smem_u32(const void* p) { return (uint32_t)__cvta_generic_to_shared(p); }
__device__ __forceinline__ void mbar_init(uint32_t bar, uint32_t count) {
  asm volatile("mbarrier.init.shared::cta.b64 [%0], %1;\n" ::"r"(bar), "r"(count) : "memory");
}
__device__ __forceinline__ void mbar_expect_tx(uint32_t bar, uint32_t bytes) {
  asm volatile("mbarrier.arrive.expect_tx.shared::cta.b64 _, [%0], %1;\n" ::"r"(bar), "r"(bytes) : "memory");
}
__device__ __forceinline__ void mbar_wait(uint32_t bar, uint32_t parity = 0) {
  uint32_t done;
#pragma unroll 1
  for (uint32_t spin = 0; spin < (1u << 22); spin++) {
    asm volatile(
        "{\n.reg .pred p;\n"
        "mbarrier.try_wait.parity.shared::cta.b64 p, [%1], %2;\n"
        "selp.u32 %0, 1, 0, p;\n}\n"
        : "=r"(done)
        : "r"(bar), "r"(parity)
        : "memory");
    if (done) return;
  }
  __trap();
}
__device__ __forceinline__ uint32_t clock32() {
  uint32_t c;
  asm volatile("mov.u32 %0, %%clock;\n" : "=r"(c)::"memory");
  return c;
}
__device__ __forceinline__ void wait_until(uint32_t t0, uint32_t dt) {
  while (clock32() - t0 < dt) __nanosleep(50);
}
__device__ __forceinline__ void tma_load_3d(uint32_t dst, const CUtensorMap* tm, uint32_t bar, int c0, int c1, int c2) {
  asm volatile(
      "cp.async.bulk.tensor.3d.shared::cluster.global.mbarrier::complete_tx::bytes [%0], [%1, {%3, %4, %5}], [%2];\n" ::"r"(dst),
      "l"(reinterpret_cast<uint64_t>(tm)), "r"(bar), "r"(c0), "r"(c1), "r"(c2)
      : "memory");
}
__device__ __forceinline__ void tma_load_5d(uint32_t dst, const CUtensorMap* tm, uint32_t bar, int c, int kj, int ki) {
  asm volatile(
      "cp.async.bulk.tensor.5d.shared::cluster.global.mbarrier::complete_tx::bytes [%0], [%1, {%3, %4, %3, %5, %6}], [%2];\n" ::"r"(dst),
      "l"(reinterpret_cast<uint64_t>(tm)), "r"(bar), "r"(0), "r"(c), "r"(kj), "r"(ki)
      : "memory");
}
__device__ __forceinline__ void tma_load_4d(uint32_t dst, const CUtensorMap* tm, uint32_t bar, int c1, int c2, int c3) {
  asm volatile(
      "cp.async.bulk.tensor.4d.shared::cluster.global.mbarrier::complete_tx::bytes [%0], [%1, {%3, %4, %5, %6}], [%2];\n" ::"r"(dst),
      "l"(reinterpret_cast<uint64_t>(tm)), "r"(bar), "r"(0), "r"(c1), "r"(c2), "r"(c3)
      : "memory");
}
template <int BYTES>
__device__ __forceinline__ void bulk_load(uint32_t dst, const void* src, uint32_t bar) {
  asm volatile("cp.async.bulk.shared::cluster.global.mbarrier::complete_tx::bytes [%0], [%1], %3, [%2];\n" ::"r"(dst), "l"(src),
               "r"(bar), "n"(BYTES)
               : "memory");
}
__device__ __forceinline__ void tma_store3(const CUtensorMap* tm, uint32_t src, int c0, int c1, int c2) {
  asm volatile("cp.async.bulk.tensor.3d.global.shared::cta.bulk_group [%0, {%2, %3, %4}], [%1];\n" ::"l"(
                   reinterpret_cast<uint64_t>(tm)),
               "r"(src), "r"(c0), "r"(c1), "r"(c2)
               : "memory");
}
__device__ __forceinline__ void tma_store(const CUtensorMap* tm, uint32_t src, int c1, int c2) {
  asm volatile("cp.async.bulk.tensor.4d.global.shared::cta.bulk_group [%0, {%2, %3, %4, %2}], [%1];\n" ::"l"(
                   reinterpret_cast<uint64_t>(tm)),
               "r"(src), "r"(0), "r"(c1), "r"(c2)
               : "memory");
}
__device__ __forceinline__ uint64_t w_desc(uint32_t saddr) {
  return (uint64_t)((saddr & 0x3FFFF) >> 4) | ((uint64_t)(1024 >> 4) << 16) | ((uint64_t)(512 >> 4) << 32) | ((uint64_t)2 << 62);
}
__device__ __forceinline__ uint64_t a_desc(uint32_t saddr) {
  return (uint64_t)((saddr & 0x3FFFF) >> 4) | ((uint64_t)1 << 16) | ((uint64_t)(512 >> 4) << 32) | ((uint64_t)2 << 62);
}
#define ACC_OPERANDS(c, d)                                                                                        \
  c(d[0]), c(d[1]), c(d[2]), c(d[3]), c(d[4]), c(d[5]), c(d[6]), c(d[7]), c(d[8]),      \
      c(d[9]), c(d[10]), c(d[11]), c(d[12]), c(d[13]), c(d[14]), c(d[15]), c(d[16]),       \
      c(d[17]), c(d[18]), c(d[19]), c(d[20]), c(d[21]), c(d[22]), c(d[23]), c(d[24]),      \
      c(d[25]), c(d[26]), c(d[27]), c(d[28]), c(d[29]), c(d[30]), c(d[31]), c(d[32]),      \
      c(d[33]), c(d[34]), c(d[35]), c(d[36]), c(d[37]), c(d[38]), c(d[39]), c(d[40]),      \
      c(d[41]), c(d[42]), c(d[43]), c(d[44]), c(d[45]), c(d[46]), c(d[47])
#define ACC_LIST                                                                   \
  "{%0, %1, %2, %3, %4, %5, %6, %7, %8, %9, %10, %11, %12, %13, %14, %15, "        \
  "%16, %17, %18, %19, %20, %21, %22, %23, %24, %25, %26, %27, %28, %29, %30, %31, " \
  "%32, %33, %34, %35, %36, %37, %38, %39, %40, %41, %42, %43, %44, %45, %46, %47}, "
__device__ __forceinline__ void wgmma_ss(float* d, uint64_t adesc, uint64_t bdesc, int accumulate = 1) {
  asm volatile(
      "{\n.reg .pred p;\nsetp.ne.b32 p, %50, 0;\n"
      "wgmma.mma_async.sync.aligned.m64n96k16.f32.bf16.bf16 " ACC_LIST "%48, %49, p, 1, 1, 0, 1;\n}\n"
      : ACC_OPERANDS("+f", d)
      : "l"(adesc), "l"(bdesc), "r"(accumulate));
}
__device__ __forceinline__ void wgmma_fence() { asm volatile("wgmma.fence.sync.aligned;\n" ::: "memory"); }
__device__ __forceinline__ void wgmma_commit() { asm volatile("wgmma.commit_group.sync.aligned;\n" ::: "memory"); }
template <int N>
__device__ __forceinline__ void wgmma_wait() { asm volatile("wgmma.wait_group.sync.aligned %0;\n" ::"n"(N) : "memory"); }
__device__ __forceinline__ void acc_fence(float* d) {
#pragma unroll
  for (int i = 0; i < 48; i++) asm volatile("" : "+f"(d[i])::"memory");
}
__device__ __forceinline__ void arrive_if(uint32_t bar) {
  asm volatile("{\n.reg .pred p;\nsetp.ne.u32 p, %0, 0;\n@p mbarrier.arrive.shared::cluster.b64 _, [%0];\n}\n" ::"r"(bar) : "memory");
}
__device__ __forceinline__ void lds128(uint32_t* v, uint32_t addr) {
  asm volatile("ld.shared.v4.b32 {%0, %1, %2, %3}, [%4];\n" : "=r"(v[0]), "=r"(v[1]), "=r"(v[2]), "=r"(v[3]) : "r"(addr) : "memory");
}
__device__ __forceinline__ void sts128(uint32_t addr, const uint32_t* v) {
  asm volatile("st.shared.v4.b32 [%0], {%1, %2, %3, %4};\n" ::"r"(addr), "r"(v[0]), "r"(v[1]), "r"(v[2]), "r"(v[3]) : "memory");
}
__device__ __forceinline__ __nv_bfloat162 as_bf2(uint32_t v) { return *reinterpret_cast<__nv_bfloat162*>(&v); }
__device__ __forceinline__ uint32_t as_u32(__nv_bfloat162 v) { return *reinterpret_cast<uint32_t*>(&v); }
__device__ __forceinline__ uint32_t hfma2(uint32_t a, uint32_t b, uint32_t c) { return as_u32(__hfma2(as_bf2(a), as_bf2(b), as_bf2(c))); }
__device__ __forceinline__ uint32_t pack2(float a, float b) { return as_u32(__floats2bfloat162_rn(a, b)); }
__device__ __forceinline__ bool elect_one() {
  uint32_t r;
  asm volatile("{\n.reg .pred p;\nelect.sync _|p, 0xffffffff;\nselp.u32 %0, 1, 0, p;\n}\n" : "=r"(r));
  return r != 0;
}
__device__ __forceinline__ void wgmma_rs(float* d, const uint32_t* a, uint64_t bdesc, int accumulate = 1) {
  asm volatile(
      "{\n.reg .pred p;\nsetp.ne.b32 p, %53, 0;\n"
      "wgmma.mma_async.sync.aligned.m64n96k16.f32.bf16.bf16 " ACC_LIST "{%48, %49, %50, %51}, %52, p, 1, 1, 1;\n}\n"
      : ACC_OPERANDS("+f", d)
      : "r"(a[0]), "r"(a[1]), "r"(a[2]), "r"(a[3]), "l"(bdesc), "r"(accumulate));
}
__device__ __forceinline__ void ldsm4(uint32_t* r, uint32_t addr) {
  asm volatile("ldmatrix.sync.aligned.m8n8.x4.shared.b16 {%0, %1, %2, %3}, [%4];\n"
               : "=r"(r[0]), "=r"(r[1]), "=r"(r[2]), "=r"(r[3])
               : "r"(addr)
               : "memory");
}
__device__ __forceinline__ void lds64(uint32_t* v, uint32_t addr) {
  asm volatile("ld.shared.v2.b32 {%0, %1}, [%2];\n" : "=r"(v[0]), "=r"(v[1]) : "r"(addr) : "memory");
}
__device__ __forceinline__ void sts32(uint32_t addr, uint32_t v) {
  asm volatile("st.shared.u32 [%0], %1;\n" ::"r"(addr), "r"(v) : "memory");
}
__device__ __forceinline__ uint32_t hadd2(uint32_t a, uint32_t b) { return as_u32(__hadd2(as_bf2(a), as_bf2(b))); }
__device__ __forceinline__ uint32_t hsub2(uint32_t a, uint32_t b) { return as_u32(__hsub2(as_bf2(a), as_bf2(b))); }
__device__ __forceinline__ uint32_t hmin2(uint32_t a, uint32_t b) { return as_u32(__hmin2(as_bf2(a), as_bf2(b))); }
__device__ __forceinline__ uint32_t hmax2(uint32_t a, uint32_t b) { return as_u32(__hmax2(as_bf2(a), as_bf2(b))); }
__device__ __forceinline__ uint32_t hfma2_lo(uint32_t w, uint32_t a, uint32_t c) {
  return as_u32(__hfma2(__low2bfloat162(as_bf2(w)), as_bf2(a), as_bf2(c)));
}
__device__ __forceinline__ uint32_t hfma2_hi(uint32_t w, uint32_t a, uint32_t c) {
  return as_u32(__hfma2(__high2bfloat162(as_bf2(w)), as_bf2(a), as_bf2(c)));
}
__device__ __forceinline__ uint32_t prmt(uint32_t a, uint32_t b, uint32_t sel) {
  uint32_t r;
  asm("prmt.b32 %0, %1, %2, %3;\n" : "=r"(r) : "r"(a), "r"(b), "r"(sel));
  return r;
}
__device__ __forceinline__ constexpr uint32_t tap_delta(int a, int b) {
  return (a == 0 ? 0xbf80u : a == 1 ? 0u : 0x3f80u) | (b == 0 ? 0xbf800000u : b == 1 ? 0u : 0x3f800000u);
}
__device__ __forceinline__ int thread_id() {
  int t;
  asm volatile("mov.u32 %0, %%tid.x;\n" : "=r"(t));
  return t ^ FLIP;
}
__device__ __forceinline__ void proxy_fence() { asm volatile("fence.proxy.async.shared::cta;\n" ::: "memory"); }
template <int PITCH>
__device__ __forceinline__ void stage16(const float* acc, int jp, uint32_t stg) {
  uint32_t pk[4];
#pragma unroll
  for (int i = 0; i < 4; i++) pk[i] = pack2(acc[jp * 8 + i * 2], acc[jp * 8 + i * 2 + 1]);
  asm volatile("stmatrix.sync.aligned.m8n8.x4.shared.b16 [%0], {%1, %2, %3, %4};\n" ::"r"((stg ^ ((jp & 1) * 32)) + (jp >> 1) * PITCH),
               "r"(pk[0]), "r"(pk[1]), "r"(pk[2]), "r"(pk[3])
               : "memory");
}
__device__ __forceinline__ uint32_t swz(uint32_t a, uint32_t chunk) { return a | (((chunk ^ (a >> 7)) & 3) << 4); }

__device__ __forceinline__ void v_load(uint32_t (*d)[2], const uint32_t* a, uint32_t a5, uint32_t off) {
#pragma unroll
  for (int j = 0; j < 6; j++) lds64(d[j], (j == 5 ? a5 : a[j & 3]) + (j >> 2) * 4 * PLANE + off);
}
__device__ __forceinline__ void sts64_if(uint32_t addr, uint32_t a, uint32_t b, int on) {
  asm volatile("{\n.reg .pred p;\nsetp.ge.s32 p, %3, 0;\n@p st.shared.v2.b32 [%0], {%1, %2};\n}\n" ::"r"(addr), "r"(a), "r"(b), "r"(on) : "memory");
}
__device__ __forceinline__ void v_store(uint32_t (*d)[2], const uint32_t* a, uint32_t o05, uint32_t o34, uint32_t off, int on = 0) {
#pragma unroll
  for (int i = 0; i < 2; i++)
    asm volatile(
        "{\n.reg .b32 p, q, r, c;\n"
        "add.rn.bf16x2 %0, %0, %4;\n"
        "add.rn.bf16x2 %5, %5, %1;\n"
        "mov.b32 c, 0xc080c080;\n"
        "fma.rn.bf16x2 p, c, %2, %4;\n"
        "fma.rn.bf16x2 q, c, %1, %3;\n"
        "mov.b32 c, 0xc088c088;\n"
        "fma.rn.bf16x2 %0, c, %2, %0;\n"
        "fma.rn.bf16x2 %5, c, %3, %5;\n"
        "mov.b32 c, 0xbe80be80;\n"
        "fma.rn.bf16x2 r, c, %2, %4;\n"
        "fma.rn.bf16x2 %3, c, %1, %3;\n"
        "mov.b32 c, 0x3f003f00;\n"
        "fma.rn.bf16x2 %1, c, q, p;\n"
        "mov.b32 c, 0xbf00bf00;\n"
        "fma.rn.bf16x2 %2, c, q, p;\n"
        "mov.b32 c, 0x40004000;\n"
        "fma.rn.bf16x2 %4, c, %3, r;\n"
        "mov.b32 c, 0xc000c000;\n"
        "fma.rn.bf16x2 %3, c, %3, r;\n}\n"
        : "+r"(d[0][i]), "+r"(d[1][i]), "+r"(d[2][i]), "+r"(d[3][i]), "+r"(d[4][i]), "+r"(d[5][i]));
  sts64_if(a[0] + o05 + off, d[0][0], d[0][1], on);
  sts64_if(a[1] + o05 + off, d[5][0], d[5][1], on);
  sts64_if(a[2] + off, d[1][0], d[1][1], on);
  sts64_if(a[3] + off, d[2][0], d[2][1], on);
  sts64_if(a[0] + o34 + off, d[4][0], d[4][1], on);
  sts64_if(a[1] + o34 + off, d[3][0], d[3][1], on);
}
__device__ __forceinline__ void u_math16(const uint32_t (*g)[4], uint32_t dst) {
#pragma unroll
  for (int h = 0; h < 2; h++) {
    uint32_t u[2][4];
#pragma unroll
    for (int i = 0; i < 4; i++) {
      const uint32_t s = hfma2(0x3e803e80u, g[2 - h * 2][i], g[h * 2][i]);
      u[0][i] = hfma2(0x3f003f00u, g[1][i], s);
      u[1][i] = hfma2(0xbf00bf00u, g[1][i], s);
    }
    sts128(dst + h * 2 * SLOT, u[0]);
    sts128(dst + (h * 2 + 1) * SLOT, u[1]);
  }
}
__device__ __forceinline__ uint32_t u_src(int t) {
  const int c = t >= 576, q = t - c * 576, b = q >> 6, kj = (b * 11) >> 5;
  return SM_RAW + c * 3072 + kj * (6144 - 192) + b * 64 + ((q >> 2) & 15) * 192 + (q & 3) * 16;
}
__device__ __forceinline__ uint32_t u_dst(int t) { return SM_W + (t >= 576 ? 3 * SLOT : 0) + (t ^ ((t >> 3) & 3)) * 16; }

__device__ __forceinline__ void ldg128(uint32_t* v, const uint4* p) {
  asm volatile("ld.global.nc.v4.b32 {%0, %1, %2, %3}, [%4];\n" : "=r"(v[0]), "=r"(v[1]), "=r"(v[2]), "=r"(v[3]) : "l"(p));
}
__device__ __forceinline__ uint32_t lds32(uint32_t addr) {
  uint32_t v;
  asm volatile("ld.shared.u32 %0, [%1];\n" : "=r"(v) : "r"(addr) : "memory");
  return v;
}
__device__ __forceinline__ void ldsm4_if(uint32_t* r, uint32_t addr, uint32_t on) {
  asm volatile(
      "{\n.reg .pred p;\nsetp.ne.u32 p, %5, 0;\n"
      "@p ldmatrix.sync.aligned.m8n8.x4.shared.b16 {%0, %1, %2, %3}, [%4];\n}\n"
      : "+r"(r[0]), "+r"(r[1]), "+r"(r[2]), "+r"(r[3])
      : "r"(addr), "r"(on)
      : "memory");
}
__device__ __forceinline__ uint32_t hmul2_lo(uint32_t w, uint32_t a) { return as_u32(__hmul2(__low2bfloat162(as_bf2(w)), as_bf2(a))); }
__device__ __forceinline__ uint32_t clip2(uint32_t p) { return hmin2(hmax2(p, 0u), 0x435f435fu); }
__device__ __forceinline__ uint32_t frac2(uint32_t pos) {
  const float py = bf16lo(pos), px = bf16hi(pos);
  return __byte_perm(__float_as_uint(py - floorf(py)), __float_as_uint(px - floorf(px)), 0x7632);
}
__device__ __forceinline__ void coefs(uint32_t w, uint32_t& p0, uint32_t& p1) {
  const uint32_t o = hsub2(0x3f803f80u, w), xa = __byte_perm(o, w, 0x7632);
  p0 = hmul2_lo(o, xa);
  p1 = hmul2_lo(w, xa);
}
__device__ __forceinline__ uint32_t blend(uint32_t p0, uint32_t p1, uint32_t t, uint32_t g, uint32_t h, uint32_t k) {
  return hfma2_hi(p1, k, hfma2_lo(p1, h, hfma2_hi(p0, g, hmul2_lo(p0, t))));
}
__device__ __forceinline__ void st_pair(uint2* p, uint32_t a, uint32_t b) {
  asm volatile("{\n.reg .b64 v;\nmov.b64 v, {%1, %2};\nst.relaxed.gpu.global.b64 [%0], v;\n}\n" ::"l"(p), "r"(a), "r"(b) : "memory");
}
__device__ __forceinline__ void ld_pair(uint32_t* v, const uint2* p) {
  asm volatile("{\n.reg .b64 v;\nld.relaxed.gpu.global.b64 v, [%2];\nmov.b64 {%0, %1}, v;\n}\n" : "=r"(v[0]), "=r"(v[1]) : "l"(p) : "memory");
}
__device__ __forceinline__ uint32_t request(Scratch* scr, uint32_t slot, uint32_t pos, int h, int w, int tap) {
  if (slot < QUEUE) st_pair(scr->req + slot, pos, 0x80000000u | (h << 12) | (w << 4) | tap);
  return slot;
}
__device__ __forceinline__ uint32_t count_up(uint32_t addr) {
  uint32_t i;
  asm volatile("atom.shared.add.u32 %0, [%1], 1;\n" : "=r"(i) : "r"(addr) : "memory");
  return i;
}
__device__ __forceinline__ void patch(uint32_t bar, uint32_t id, uint32_t n, uint32_t base, uint32_t pitch, uint32_t ctl, int lane) {
  uint32_t todo = __ballot_sync(0xffffffffu, id < n);
#pragma unroll 1
  do {
    const int i0 = __ffs(todo) - 1;
    todo &= todo - 1;
    const uint32_t p0 = __reduce_max_sync(0xffffffffu, lane == i0 ? id : 0u), other = todo & __ballot_sync(0xffffffffu, id != p0);
    const int i1 = __ffs(other) - 1;
    todo &= ~(other & -other);
    const uint32_t p1 = __reduce_max_sync(0xffffffffu, lane == i1 ? id : 0u);
    const bool on = (lane & 15) < 12 && (lane < 16 || other);
    const uint32_t a = on ? swz(base + ((lane >> 2) & 3) * pitch + (lane < 16 ? p0 : p1) * 64, lane) : ctl + O_LST + 64;
    uint32_t v[4], c[4];
    lds128(c, swz(ctl + O_COR + ((lane >> 2) & 3) * 1024 + (lane < 16 ? i0 : i1) * 64, lane));
    mbar_wait(bar);
    lds128(v, a);
#pragma unroll
    for (int k = 0; k < 4; k++) v[k] = hadd2(v[k], c[k]);
    sts128(a, v);
    __syncwarp();
  } while (todo);
  proxy_fence();
  __syncwarp();
}

__host__ __device__ __forceinline__ int role_of(int b) {
  const int k = b >> 1;
  return b & 1 ? (k < 4 ? k + 56 : k < 60 ? k - 4 : k + 66) : k + 60;
}

__device__ __forceinline__ int low_bits(const void* p) {
  int r;
  asm volatile("{\n.reg .b32 h;\nmov.b64 {%0, h}, %1;\nand.b32 %0, %0, 15;\n}\n" : "=r"(r) : "l"(p));
  return r;
}
struct Maps {
  Scratch* scr;
  CUtensorMap x, w, wc, out, off, col, gx, gout;
  CUtensorMap bx[2], bw[2], bout[2];
};

__global__ void __launch_bounds__(NTHREADS, 1)
dcn_kernel(const uint4* __restrict__ x, const uint32_t* __restrict__ offs, uint32_t* tsp,
           const uint32_t never, const __grid_constant__ Maps tm) {
  extern __shared__ __align__(1024) uint8_t smem[];
  constexpr uint32_t sbase = 1024;
  constexpr uint32_t bars = sbase + SM_BAR;
  const uint32_t tstart = clock32();
  const int tid = thread_id();
  if (PFM == 1 || PFM == 2) asm volatile("prefetch.tensormap [%0];\n" ::"l"(reinterpret_cast<uint64_t>(&tm.w)) : "memory");
  if (PFM == 2) asm volatile("prefetch.tensormap [%0];\n" ::"l"(reinterpret_cast<uint64_t>(&tm.x)) : "memory");
  const int wid = __shfl_sync(0xffffffffu, (tid >> 5) + (PFM == 3 ? low_bits(&tm.w) : 0), 0);
  const bool first = wid == 12 && (!(blockIdx.x & 1) || blockIdx.x >= 120);
  if (EARLYW && first && elect_one()) {
    mbar_init(bars + (B_WF + 1) * 8, 1);
    tma_load_3d(sbase + SM_RAW, &tm.w, bars + (B_WF + 1) * 8, 0, 0, 0);
  }
  int bx = blockIdx.x;
  if (EARLYW) asm volatile("mov.u32 %0, %%ctaid.x;\n" : "=r"(bx));
  const int cta = role_of(bx);
  const int lane = tid & 31;
  const int ri = cta - NI, ry = ri / 3, x0 = 32 + (ri - ry * 3) * 64, y0 = 32 + ry * 8;
  const int band = cta >= 24, g0 = 32 + (cta - band * 24) * 8;
  if (first) {
    const bool one = elect_one();
    if (one) {
      if (!EARLYW) mbar_init(bars + (B_WF + 1) * 8, 1);
      mbar_init(bars + B_XF * 8, 1);
      mbar_init(bars + (B_XF + 1) * 8, 1);
      asm volatile("fence.mbarrier_init.release.cluster;\n" ::: "memory");
      if (!EARLYW) tma_load_3d(sbase + SM_RAW, &tm.w, bars + (B_WF + 1) * 8, 0, 0, 0);
      tma_load_3d(sbase + SM_V, &tm.x, bars + B_XF * 8, 0, x0 - 1, y0 + (ry & 1) * 4 - 1);
      mbar_expect_tx(bars + (B_WF + 1) * 8, 6 * SLOT);
      mbar_expect_tx(bars + B_XF * 8, UNIT);
      mbar_expect_tx(bars + (B_XF + 1) * 8, UNIT);
    }
    asm volatile("bar.arrive 0, 512;\n" ::: "memory");
    if (one) {
      while (clock32() - tstart < X1T) {}
      tma_load_3d(sbase + SM_V + UNIT, &tm.x, bars + (B_XF + 1) * 8, 0, x0 - 1, y0 + (~ry & 1) * 4 - 1);
    }
  }
  if (wid == 12 && cta >= NI - 4 && cta < NI) {
    if (elect_one()) {
#pragma unroll
      for (int c = 0; c < 5; c++) mbar_init(bars + c * 8, 1);
      asm volatile("fence.mbarrier_init.release.cluster;\n" ::: "memory");
    }
    asm volatile("bar.arrive 0, 512;\n" ::: "memory");
    if (elect_one()) {
      if (cta < NI - 1) {
#pragma unroll
        for (int c = 0; c < 4; c++) {
          mbar_expect_tx(bars + c * 8, SLOT);
          tma_load_4d(sbase + (18 + c) * SLOT, &tm.wc, bars + c * 8, (c + 2) * 24, cta - (NI - 4), 0);
        }
      } else {
        mbar_expect_tx(bars + 3 * 8, 28672 + 16128);
        tma_load_3d(sbase + 18 * SLOT, &tm.col, bars + 3 * 8, 0, 9, 0);
        bulk_load<16128>(sbase + 18 * SLOT + 28672, offs + 32 * IW * 9, bars + 3 * 8);

      }
    }
  }
  if (cta >= NI - 4 && cta < NI) {
    const int kj = cta - (NI - 4);
    if (wid != 12) asm volatile("bar.sync 0, 512;\n" ::: "memory");
    auto get_epoch = [&]() {
      uint32_t e;
      asm volatile("ld.relaxed.gpu.global.u32 %0, [%1];\n" : "=r"(e) : "l"(tm.scr->ready + (kj == 3 ? 3 : 2)) : "memory");
      return (e & ~127u) + 128;
    };
    uint32_t epoch;
    auto load_w = [&]() {
      mbar_expect_tx(bars + 4 * 8, 18 * SLOT);
#pragma unroll
      for (int sl = 0; sl < 3; sl++) tma_load_3d(sbase + sl * 6 * SLOT, &tm.w, bars + 4 * 8, 0, sl * 48, 0);
    };
    if (kj == 3) {
      constexpr uint32_t src = sbase + 18 * SLOT, lst = src + 28672 + 16128;
      uint32_t big = 0;
      epoch = get_epoch();
      if (tid < GRID) sts32(bars + 64 + tid * 4, 0);
      asm volatile("bar.sync 1, 512;\n" ::: "memory");
      if (tid == 0) load_w();
      mbar_wait(bars + 3 * 8);
#pragma unroll
      for (int i = 0; i < 6; i++) {
        const uint32_t p = tid + i * 512;
        uint32_t v[4];
        lds128(v, src + p * 16);
        const uint32_t lim = i == 0 && tid < 256 ? 0x42804080u : i >= 3 && (p - 1792 < 72 || p - 2296 < 72) ? 0x40804280u : 0x42804280u;
        uint32_t over = 0;
#pragma unroll
        for (int k = 0; k < 4; k++) over |= (v[k] & 0x7fff7fffu) + lim;
        if ((over & 0x80008000u) && (p < 1792 ? (tid & 7) < 5 : p < 2800)) big |= 1u << i;
      }
#pragma unroll 1
      for (; big; big &= big - 1) {
        const uint32_t i = count_up(bars + 64 + 57 * 4);
        if (i < 1024) sts32(lst + i * 4, tid + (__ffs(big) - 1) * 512);
      }
      __syncwarp();
      asm volatile("bar.sync 1, %0;\n" ::"r"(512 + (epoch & never)) : "memory");
      const uint32_t n = lds32(bars + 64 + 57 * 4);
      if (n > 1024 && tid < GRID && (tid < 56 || tid >= NI)) sts32(bars + 64 + tid * 4, FAILED);
#pragma unroll 1
      for (uint32_t c = tid; c < n * 4 && n <= 1024; c += 512) {
        const uint32_t wq = lds32(lst + (c & ~3u)) * 4 + (c & 3), col = wq < 7168;
        const uint32_t wi = col ? wq & 31 : wq - 7168, px = (wi * 7282) >> 16, tap = wi - px * 9;
        const int eh = col ? wq >> 5 : 32 + (px >= 224), ew = col ? 32 + px : px >= 224 ? px - 224 : px, ki = (tap * 11) >> 5;
        const uint32_t gp = pack2((float)(eh + ki - 1), (float)(ew + (int)tap - ki * 3 - 1));
        const uint32_t pos = clip2(hadd2(gp, lds32(src + wq * 4)));
        const uint32_t d = __byte_perm(hsub2(pos, hmin2(gp, 0x435f435fu)), 0, ew < 32 ? 0x1032 : 0x3210) & 0x7fff7fffu;
        if (d <= (min(eh, ew) < 32 ? 0x3f80u : 0u) || (col && (px >= 2 || eh >> 1 == 16))) continue;
        const int client = eh < 32 ? 0 : ew < 32 ? 24 : NI + ((eh - 32) >> 3) * 3 + ((ew - 32) >> 6);
        const uint32_t i = count_up(bars + 64 + client * 4);
        if (i >= MAXEX) continue;
        const uint32_t slot = count_up(bars + 64 + 56 * 4);
        const uint32_t id = eh < 32 ? eh * 8 + ew - 32 : ew < 32 ? ew * 8 + eh - 32 : (eh & 7) * 64 + ((ew - 32) & 63);
        st_pair(tm.scr->mail[client] + i, id | (request(tm.scr, slot < EARLY ? slot : QUEUE, pos, eh, ew, tap) << 16), epoch);
      }
      __syncwarp();
      asm volatile("bar.sync 1, %0;\n" ::"r"(512 + (epoch & never)) : "memory");
      if (tid < GRID) st_pair(tm.scr->mail[tid] + MAXEX, lds32(bars + 64 + tid * 4), epoch);
      if (tid == 0) {
        tm.scr->ready[3] = epoch;
        tm.scr->ready[8 + ((epoch >> 7) & 1 ^ 1)] = 0;
      }
      TSE(2);
    } else if (wid < 12) {
      const int half = wid >= 6, q = tid - half * 192;
      const uint32_t lin = (q >> 6) * 64 + ((q >> 2) & 15) * 192 + (q & 3) * 16;
      const int e = kj * 192 + (q ^ ((q >> 3) & 3));
#pragma unroll 1
      for (int c = half - 2; c < 4; c += 2) {
        uint4 g[3], u[4];
        if (c >= 0) mbar_wait(bars + c * 8);
#pragma unroll
        for (int k = 0; k < 3; k++) lds128(&g[k].x, sbase + (18 + c) * SLOT + k * 3072 + lin);
#pragma unroll
        for (int i = 0; i < 4; i++) {
            const uint32_t s = hfma2(0x3e803e80u, (&g[2].x)[i], (&g[0].x)[i]), t = hfma2(0x3e803e80u, (&g[0].x)[i], (&g[2].x)[i]);
            (&u[0].x)[i] = hfma2(0x3f003f00u, (&g[1].x)[i], s);
            (&u[1].x)[i] = hfma2(0xbf00bf00u, (&g[1].x)[i], s);
            (&u[2].x)[i] = hfma2(0x3f003f00u, (&g[1].x)[i], t);
            (&u[3].x)[i] = hfma2(0xbf00bf00u, (&g[1].x)[i], t);
        }
        if (c >= 2) asm volatile("bar.sync 2, 416;\n" ::: "memory");
#pragma unroll
        for (int k = 0; k < 4; k++)
          asm volatile("{\n.reg .pred p;\nsetp.ge.s32 p, %5, 0;\n@p st.global.v4.b32 [%0], {%1, %2, %3, %4};\n}\n" ::"l"(tm.scr->u + (c * 4 + k) * 576 + e),
                       "r"(u[k].x), "r"(u[k].y), "r"(u[k].z), "r"(u[k].w), "r"(c) : "memory");
        if (c >= 0) asm volatile("bar.arrive 1, 416;\n" ::: "memory");
      }
      epoch = get_epoch();
      if (!half) {
        mbar_wait(bars + 4 * 8);
#pragma unroll 6
        for (int c = 0; c < 12; c++) {
          uint4 v;
          lds128(&v.x, sbase + (c % 6 >> 1) * 6 * SLOT + (c / 6 * 6 + kj) * 6144 + (c & 1) * 3072 + lin);
          tm.scr->w[c * 576 + e] = v;
        }
      }
      asm volatile("bar.arrive 3, %0;\n" ::"r"(512 + (epoch & never)) : "memory");
    } else if (wid == 12) {
      epoch = get_epoch();
#pragma unroll 1
      for (int r = 0; r < 3; r++) {
        asm volatile("bar.sync %0, %1;\n" ::"r"(r < 2 ? 1 : 3), "r"((r < 2 ? 416 : 512) + (epoch & never)) : "memory");
        if (elect_one()) {
          asm volatile("red.release.gpu.global.add.u32 [%0], %1;\n" ::"l"(tm.scr->ready + r), "r"(kj ? 32 : 64) : "memory");
          if (r == WAT) load_w();
        }
        __syncwarp();
        if (r == 0) asm volatile("bar.arrive 2, 416;\n" ::: "memory");
      }
    } else {
      epoch = get_epoch();
      asm volatile("bar.arrive 3, %0;\n" ::"r"(512 + (epoch & never)) : "memory");
    }
    const uint32_t dl = sbase + 18 * SLOT + 4 * 12288 + wid * 384;
#pragma unroll 1
    for (int slot = (wid == 12 ? 15 : wid > 12 ? 15 - wid : 14 - wid) * 4 + (kj ^ 3); slot < QUEUE; slot += 64) {
      uint2 rq;
#pragma unroll 1
      for (uint32_t spin = 0;; spin++) {
        uint32_t done[2];
        ld_pair(&rq.x, tm.scr->req + slot);
        if (slot < EARLY) {
          ld_pair(done, tm.scr->mail[56] + MAXEX);
          if (rq.y || (done[1] == epoch && slot >= done[0])) break;
        } else {
          asm volatile("ld.acquire.gpu.global.u32 %0, [%1];\n" : "=r"(done[1]) : "l"(tm.scr->ready + 6) : "memory");
          if (rq.y) break;
          if (done[1] == epoch) {
            asm volatile("ld.relaxed.gpu.global.u32 %0, [%1];\n" : "=r"(done[0]) : "l"(tm.scr->ready + 8 + ((epoch >> 7) & 1)) : "memory");
            if (slot - EARLY >= done[0]) break;
          }
        }
        if (spin > (1u << 22)) __trap();
        __nanosleep(100);
      }
      if (!rq.y) continue;
      __syncwarp();
      if (lane == 0) tm.scr->req[slot] = make_uint2(0, 0);
      const int tap = rq.y & 15, ki = (tap * 11) >> 5, gy = (int)bf16lo(rq.x), gx = (int)bf16hi(rq.x);
      const int cy = min(max((int)((rq.y >> 12) & 255) + ki - 1, 0), IH - 1), cx = min(max((int)((rq.y >> 4) & 255) + tap - ki * 3 - 1, 0), IW - 1);
      if (lane < 24) {
        const uint2* pc = reinterpret_cast<const uint2*>(x) + lane;
        const int p = (gy * IW + gx) * 24, sx = gx < IW - 1 ? 24 : 0, sy = gy < IH - 1 ? IW * 24 : 0;
        const uint2 v0 = __ldg(pc + p), v1 = __ldg(pc + p + sx), v2 = __ldg(pc + p + sy), v3 = __ldg(pc + p + sy + sx);
        const uint2 c = __ldg(pc + (cy * IW + cx) * 24);
        uint32_t q0, q1;
        coefs(frac2(rq.x), q0, q1);
        const uint32_t d0 = hsub2(blend(q0, q1, v0.x, v1.x, v2.x, v3.x), c.x), d1 = hsub2(blend(q0, q1, v0.y, v1.y, v2.y, v3.y), c.y);
        const uint32_t dd[4] = {__byte_perm(d0, 0, 0x1010), __byte_perm(d0, 0, 0x3232), __byte_perm(d1, 0, 0x1010), __byte_perm(d1, 0, 0x3232)};
        sts128(dl + lane * 16, dd);
      }
      __syncwarp();
      mbar_wait(bars + 4 * 8);
      float sum[8] = {};
      const int l24 = min(lane, 23);
#pragma unroll 1
      for (int b = 0; b < 6; b++) {
        uint32_t part[4] = {};
#pragma unroll
        for (int i = 0; i < 8; i++) {
          uint32_t wv[4];
          lds128(wv, sbase + (b >> 1) * 6 * SLOT + tap * 6144 + (b & 1) * 3072 + i * 384 + l24 * 16);
          const uint32_t d = lds32(dl + (b * 16 + i * 2 + (l24 >= 12)) * 4);
#pragma unroll
          for (int k = 0; k < 4; k++) part[k] = hfma2(d, wv[k], part[k]);
        }
#pragma unroll
        for (int k = 0; k < 4; k++) {
          sum[k * 2] += bf16lo(part[k]);
          sum[k * 2 + 1] += bf16hi(part[k]);
        }
      }
#pragma unroll
      for (int k = 0; k < 8; k++) sum[k] += __shfl_down_sync(0xffffffffu, sum[k], 12);
      if (lane < 12) {
#pragma unroll
        for (int k = 0; k < 4; k++)
          st_pair(tm.scr->res[slot] + lane * 4 + k, pack2(sum[k * 2], sum[k * 2 + 1]), epoch);
      }
      TSE(1);
    }
    mbar_wait(bars + 4 * 8);
  } else if (wid < 8) {
    const int wg = wid >> 2, warp = wid & 3;
    if (cta < 48) {
    const int f = wid * 4 + (lane >> 3), g = g0 + (lane & 7);
    uint32_t cf[36];
    wait_until(tstart, BSLEEP);
    {
      const uint32_t* op = offs + (band ? g * IW + f : f * IW + g) * 9;
#pragma unroll
      for (int a = 0; a < 3; a++)
#pragma unroll
        for (int b = 0; b < 3; b++) cf[a * 3 + b] = __ldg(op + (band ? b * 3 + a : a * 3 + b));
    }
    asm volatile("bar.sync 0, 512;\n" ::: "memory");
    {
      const uint32_t base = pack2((float)f, (float)g), sel = band ? 0x1032u : 0x3210u;
      const uint32_t tab = sbase + SM_YT + wid * 1152;
      uint32_t bad = 0;
#pragma unroll
      for (int a = 0; a < 3; a++)
#pragma unroll
        for (int b = 0; b < 3; b++) {
          const uint32_t gp = hadd2(base, tap_delta(a, b));
          const uint32_t pos = clip2(hadd2(gp, __byte_perm(cf[a * 3 + b], 0, sel)));
          uint32_t d = hsub2(pos, hmin2(gp, 0x435f435fu));
          if ((d & 0x7fff7fffu) > 0x3f80u) {
            bad = 1;
            d = a == 0 && f == 0 ? 0x3f80u : 0u;
          }
          sts32(tab + (lane & 7) * 144 + (b * 12 + (lane >> 3) * 3 + a) * 4, (d << 16) | (d & 0x8000u ? 0x3210u : 0x7654u));
        }
      if (bad && g >= 34) sts32(bars + O_CNT, FAILED);
      __syncwarp();
      arrive_if(lane == 0 ? bars + B_OS * 8 : 0u);
      asm volatile("setmaxnreg.inc.sync.aligned.u32 224;\n");
      __syncwarp();
#pragma unroll
      for (int i = 0; i < 9; i++) lds128(cf + i * 4, tab + (lane >> 2) * 144 + i * 16);
    }
    uint32_t xa[3];
#pragma unroll
    for (int b = 0; b < 3; b++)
      xa[b] = swz(sbase + SM_YX + ((wid * 4 + (lane >> 4)) * 10 + min((lane & 7) + b, IW - g0)) * 64, (lane >> 3) & 1);
    float acc[2][48];
    uint32_t X[2][16], A[2][12];
    auto fetch = [&](uint32_t* r, uint32_t a) {
#pragma unroll
      for (int i = 0; i < 4; i++) ldsm4(r + i * 4, (a ^ ((i & 1) * 32)) + i * 1280);
    };
    uint64_t bd = w_desc(sbase);
    uint32_t wf = bars + B_WF * 8;
    mbar_wait(bars + B_XF * 8);
    TSE(0);
    fetch(X[0], xa[0]);
    mbar_wait(wf);
#pragma unroll 1
    for (int s = 0; s < 3; s++) {
#pragma unroll
      for (int n = 0; n < 6; n++) {
        const int b = n >> 1;
        if (n == 5) {
          mbar_wait(bars + (B_XF + min(s + 1, 2)) * 8);
#pragma unroll
          for (int k = 0; k < 3; k++) xa[k] += s < 2 ? YSLICE : 0;
        }
        fetch(X[~n & 1], xa[(n + 1) % 6 >> 1] ^ ((~n & 1) * 32));
        const uint32_t* xr = X[n & 1];
        uint32_t D[7][2];
#pragma unroll
        for (int j = 0; j < 7; j++)
#pragma unroll
          for (int e = 0; e < 2; e++) D[j][e] = hsub2(xr[(j + 1) * 2 + e], xr[j * 2 + e]);
#pragma unroll
        for (int t = 0; t < 2; t++) {
          wgmma_wait<1>();
#pragma unroll
          for (int a = 0; a < 3; a++)
#pragma unroll
            for (int i = 0; i < 4; i++) {
              const int o = t * 2 + (i & 1), e = i >> 1, j = o + a + 1;
              const uint32_t c = cf[b * 12 + o * 3 + a];
              A[t][a * 4 + i] = hfma2_hi(c, prmt(D[j - 1][e], D[j][e], c), xr[j * 2 + e]);
            }
          wgmma_fence();
#pragma unroll
          for (int a = 0; a < 3; a++) wgmma_rs(acc[t], A[t] + a * 4, bd + n * (SLOT >> 4) + a * 192, (n | a) ? 1 : s);
          wgmma_commit();
        }
        if (n & 1) mbar_wait(wf + (b + 1) * 8);
        if (n == 1 && s == 1 && elect_one()) arrive_if(bars + B_WE * 8);
      }
      bd += 6 * SLOT >> 4;
      wf += 24;
      if (s == YPS && wg) __nanosleep(YPN);
    }
    TSE(1);
    const int lane = thread_id() & 31;
    const uint32_t stg = sbase + wg * 3 * SLOT + (wid & 3) * 2048 + (lane & 15) * 64 + ((((lane >> 4) ^ (lane >> 1)) & 3) << 4);
    wgmma_wait<1>();
    acc_fence(acc[0]);
#pragma unroll
    for (int jp = 0; jp < 6; jp++) stage16<8192>(acc[0], jp, stg);
    wgmma_wait<0>();
    acc_fence(acc[1]);
#pragma unroll
    for (int jp = 0; jp < 6; jp++) stage16<8192>(acc[1], jp, stg + 1024);
    proxy_fence();
    __syncwarp();
    arrive_if(lane == 0 ? bars + (B_ST + wg * 4) * 8 : 0u);
    } else if (cta < NI) {
      asm volatile("bar.sync 0, 512;\n" ::: "memory");
      asm volatile("setmaxnreg.inc.sync.aligned.u32 224;\n");
    } else {
    {
      uint32_t g[3][3][4], src[3], dst[3];
#pragma unroll
      for (int r = 0; r < 3; r++) {
        src[r] = sbase + u_src(tid + r * 384);
        dst[r] = sbase + u_dst(tid + r * 384);
      }
      asm volatile("bar.sync 0, 512;\n" ::: "memory");
      mbar_wait(bars + (B_WF + 1) * 8);
#pragma unroll
      for (int r = 0; r < 3; r++) {
#pragma unroll
        for (int k = 0; k < 3; k++) lds128(g[r][k], src[r] + k * 2 * SLOT);
      }
#pragma unroll
      for (int r = 0; r < 3; r++) u_math16(g[r], dst[r]);
      proxy_fence();
      __syncwarp();
      arrive_if(lane == 0 ? bars + B_WF * 8 : 0u);
    }
    asm volatile("setmaxnreg.inc.sync.aligned.u32 224;\n");
    float m[4][48];
    const uint32_t vb = sbase + SM_V + wg * UNIT;
    const uint64_t bd0 = w_desc(sbase + SM_W), ad12 = a_desc(vb + 2 * PLANE), ad05 = a_desc(vb + (wg ? 4 * PLANE : 0));

    const uint64_t d34 = wg ? -(2 * PLANE >> 4) : 2 * PLANE >> 4;
    uint64_t ad = ad12;
    uint32_t wf = bars + B_WF * 8, a[4];
    {
      const int t = thread_id();
#pragma unroll
      for (int j = 0; j < 4; j++) a[j] = swz(vb + j * PLANE + ((t & 127) >> 3) * 64, t >> 1) + (t & 1) * 8;
    }
#pragma unroll 1
    for (int sl = 0; sl < 3; sl++) {
      {
        uint32_t d[6][2], d2[6][2], tq[4];
        const uint32_t a5 = y0 == 216 && ((wg ^ ry) & 1) ? a[0] : a[1], o34 = wg ? 0 : 4 * PLANE;
        TQ(0);
        mbar_wait(bars + (B_XF + sl * 2 + wg) * 8);
        TQ(1);
        if (CG != 2 && (CG ? wg | sl : sl)) mbar_wait(bars + (B_XR + sl * 2 + wg - 1) * 8);
        if (((SH >> ((sl * 2 + wg) * 4)) & 3) == 1) {
          v_load(d, a, a5, 1024);
          v_store(d, a, 4 * PLANE - o34, o34, 1024);
        }
        v_load(d, a, a5, 2048);
        if (CPF) v_load(d2, a, a5, 3072);
        v_store(d, a, 4 * PLANE - o34, o34, 2048);
        if (!CPF) v_load(d2, a, a5, 3072);
        v_store(d2, a, 4 * PLANE - o34, o34, 3072);
        proxy_fence();
        __syncwarp();
        if (elect_one()) arrive_if(bars + (B_XR + sl * 2 + wg) * 8);
#pragma unroll
        for (int j = 0; j < 4; j++) asm volatile("add.u32 %0, %0, %1;\n" : "+r"(a[j]) : "n"(2 * UNIT));
        TQ(2);
        mbar_wait(wf);
        TQ(3);
        mbar_wait(bars + (B_XR + sl * 2 + wg) * 8);
        if (LOCK && wg && sl == 2) asm volatile("bar.sync 6, 256;\n" ::: "memory");
      }
#pragma unroll
      for (int n = 0; n < 8; n++) {
        const int k = n & 3;
        wgmma_fence();
#pragma unroll
        for (int kj = 0; kj < 3; kj++)
          wgmma_ss(m[k], (k < 2 ? ad : ad + d34) + (k & 1) * (PLANE >> 4) + n / 4 * 2 + kj * 4, bd0 + n * (SLOT >> 4) + kj * 192, (n / 4 | kj) ? 1 : sl);
        wgmma_commit();
        if (n < 7) {
          if (sl) mbar_wait(wf + (n + 1) * 8);
          wgmma_wait<1>();
          if (warp == 0 && n) asm volatile("bar.arrive %0, 96;\n" ::"r"(7 + n) : "memory");
          if ((BUB >> n) & 1) wgmma_wait<0>();
        }
      }
      if (sl == 2 && (LOCK || wg)) asm volatile("bar.arrive %0, 256;\n" ::"r"(wg ? 4 : 6) : "memory");
      wgmma_wait<1>();
      if (warp == 0) asm volatile("bar.arrive 14, 96;\n" ::: "memory");
      wgmma_wait<0>();
      if (warp == 0) asm volatile("bar.arrive 15, 96;\n" ::: "memory");
      ad += 2 * UNIT >> 4;
      wf += 64;

    }
    const int lane = thread_id() & 31;
    const uint32_t stg = sbase + SM_X + 2 * UNIT + wg * 21504 + warp * 1024 + (lane & 15) * 64 + ((((lane >> 4) ^ (lane >> 1)) & 3) << 4);
    const uint32_t stb = lane == 0 ? bars + (B_ST + wg * 4) * 8 : 0u;
    auto publish = [&](int k) {
      proxy_fence();
      __syncwarp();
      arrive_if(stb ? stb + k * 8 : 0u);
    };
#pragma unroll
    for (int k = 0; k < 4; k++) acc_fence(m[k]);
    float dep = 0.f;
#pragma unroll
    for (int i0 = 0; i0 < 48; i0 += TG) {
      const float k0 = __uint_as_float((__float_as_uint(dep) & never) | 0xbf088889u);
      const float k1 = __uint_as_float((__float_as_uint(dep) & never) | 0xbf800000u);
#pragma unroll
      for (int i = i0; i < i0 + TG; i++) {
        m[0][i] *= k0;
        m[3][i] = fmaf(k1, m[3][i], m[2][i]);
        m[1][i] = fmaf(-8.0f / 15.0f, m[1][i], m[0][i]);
        m[2][i] = fmaf(-0.5f, m[3][i], m[2][i]);
        m[0][i] = fmaf(-0.5f, m[1][i], m[0][i]);
        m[1][i] = fmaf(4.0f / 15.0f, m[2][i], m[1][i]);
        m[0][i] = fmaf(4.0f / 15.0f, m[3][i], m[0][i]);
        m[2][i] = fmaf(0.25f, m[1][i], m[2][i]);
        m[3][i] = fmaf(0.25f, m[0][i], m[3][i]);
        dep = m[0][i];
        if ((i & 7) == 7) {
          stage16<4096>(m[2], i >> 3, stg);
          stage16<4096>(m[0], i >> 3, stg + 2 * UNIT);
        }
      }
    }
    publish(0);
    asm volatile("bar.sync %0, 256;\n" ::"r"(4 + wg) : "memory");
    uint32_t rows, ids[4];
    const uint64_t bdx = w_desc(sbase + SM_X);
    const uint32_t s05 = vb + (wg ? 4 * PLANE : 0) + warp * 1024 + (lane & 15) * 64;
#pragma unroll
    for (int j = 0; j < 12; j++) {
      float* acc = j < 6 ? m[1] : m[3];
      const int c = j % 6;
      const uint64_t ad = ad05 + (c >> 1) * (2 * UNIT >> 4) + (c & 1) * 2 + (j < 6 ? 0 : PLANE >> 4);
      const uint64_t bd = j < 3 ? bdx + j * (SLOT >> 4) : j == 3 ? bdx + ((2 * UNIT + 12288) >> 4) : bd0 + (j - 4) * (SLOT >> 4);
      if (j != 1 && j != 2) mbar_wait(bars + (B_WF + 24 + j) * 8);
      if (j == 5 || j == 11) {
        const uint32_t row = ((wg ^ ry) & 1) * 4 + (j == 5 ? 0 : 3), me = row * 64 + warp * 16 + (lane >> 2);
        if (__any_sync(0xffffffffu, rows != FAILED && ((rows >> row) & 1))) {
          uint32_t sel[4];
#pragma unroll
          for (int i = 0; i < 4; i++)
            sel[i] = (ids[(i >> 1) * 2] == me + (i & 1) * 8 ? 0x3f80u : 0u) | (ids[(i >> 1) * 2 + 1] == me + (i & 1) * 8 ? 0x3f800000u : 0u);
          mbar_wait(bars + B_CR * 8);
          wgmma_fence();
          wgmma_rs(acc, sel, w_desc(bars + O_COR));
        }
      }
      wgmma_fence();
#pragma unroll
      for (int kj = 0; kj < 3; kj++) wgmma_ss(acc, ad + kj * 4, bd + kj * 192);
      wgmma_commit();
      if (j == 1) {
        mbar_wait(bars + B_OK * 8);
        rows = lds32(bars + O_VER);
        lds64(ids, bars + O_LST + (lane & 3) * 8);
        lds64(ids + 2, bars + O_LST + 32 + (lane & 3) * 8);
      }
      if (j == 7) {
        wgmma_wait<2>();
        acc_fence(m[1]);
      }
      if (j >= 7 && j <= 9) {
#pragma unroll
        for (int jp = j * 2 - 14; jp < j * 2 - 12; jp++) stage16<2 * UNIT>(m[1], jp, swz(s05, lane >> 4));
      }
      if (j == PUB1) publish(1);
      if (HAND == j && !wg) asm volatile("bar.arrive 5, 256;\n" ::: "memory");
    }
    wgmma_wait<0>();
    acc_fence(m[3]);
    TSE(1);
#pragma unroll
    for (int jp = 0; jp < 6; jp++) stage16<2 * UNIT>(m[3], jp, swz(s05 + PLANE, lane >> 4));
    if (HAND == 12 && !wg) asm volatile("bar.arrive 5, 256;\n" ::: "memory");
    publish(2);
    }
    int rounds = 1;
    const int tid = thread_id(), lane = tid & 31;
    if (cta < 48 || cta >= NI) {
      mbar_wait(bars + B_OK * 8);
      rounds = lds32(bars + O_VER) != FAILED ? 0 : cta < 48 ? 2 : 4;
      rounds = __shfl_sync(0xffffffffu, rounds, 0);
    }
    if (rounds) {
      const bool lead = warp == 0 && elect_one();
      if (rounds > 1) {
        if (tid == 0) {
#pragma unroll
          for (int i = 0; i < 15; i++) mbar_init(bars + (B_G + i) * 8, 1);
          asm volatile("fence.mbarrier_init.release.cluster;\n" ::: "memory");
        }
        proxy_fence();
        asm volatile("bar.sync 3, 256;\n" ::: "memory");
      }
      const uint32_t win = sbase + SM_GX + wg * 3 * GSLICE, gxb = bars + (B_G + 9 + wg * 3) * 8;
      const uint64_t bd0 = w_desc(sbase);
      float acc[48];
#pragma unroll 1
      for (int r = 0; r < rounds; r++) {
        int ty, tx, bx;
        asm volatile("mov.u32 %0, %%ctaid.x;\n" : "=r"(bx));
        const int cta = role_of(bx), ry = (cta - NI) / 3, x0 = 32 + (cta - NI - ry * 3) * 64, y0 = 32 + ry * 8;
        const int band = cta >= 24, g0 = 32 + (cta - band * 24) * 8;
        if (cta >= NI) { ty = y0; tx = x0 + r * 16 + wg * 8; }
        else if (cta < 48) { ty = band ? g0 : r * 16 + wg * 8; tx = band ? r * 16 + wg * 8 : g0; }
        else { ty = (cta & 1) * 8 + wg * 16; tx = (cta & 2) * 4 + ((cta >> 2 ^ wg) & 1) * 16; }
        if (lead && rounds > 1) {
#pragma unroll 1
          for (int sl = 0; sl < 3; sl++) {
            mbar_expect_tx(gxb + sl * 8, GSLICE);
            tma_load_3d(win + sl * GSLICE, &tm.gx, gxb + sl * 8, sl * 32, tx - 2, ty - 2);
            if (r == 0) {
#pragma unroll 1
              for (int ki = 0; ki < 3; ki++) {
                if (!wg) mbar_expect_tx(bars + (B_G + sl * 3 + ki) * 8, 2 * SLOT);
                tma_load_5d(sbase + ((sl * 3 + ki) * 2 + wg) * SLOT, &tm.bw[1], bars + (B_G + sl * 3 + ki) * 8, sl * 32 + wg * 16, 0, ki);
              }
            }
          }
        }
        const int ph = ty + warp * 2 + ((lane >> 3) & 1), pw = tx + (lane & 7);
        const uint32_t* op = offs + (ph * IW + pw) * 9;
        const uint32_t base = pack2((float)ph, (float)pw);
        uint32_t ent[9], cf[36], need = 0, out = 0;
#pragma unroll
        for (int m = 0; m < 9; m++) ent[m] = __ldg(op + m);
#pragma unroll
        for (int m = 0; m < 9; m++) {
          const uint32_t pos = clip2(hadd2(hadd2(base, tap_delta(m / 3, m % 3)), ent[m])), fr = frac2(pos);
          const uint32_t iy = (int)bf16lo(pos) - (ty - 2), ix = (int)bf16hi(pos) - (tx - 2);
          out |= max(iy, ix) > 10;
          need |= ((fr >> 16 ? 1u : 0u) | (fr & 0xffffu ? 2u : 0u) | (fr >> 16 && (fr & 0xffffu) ? 4u : 0u)) << (m * 3);
          const uint32_t up = (fr & 0xffffu) >= 0x3f00u, fn = hmin2(fr, hsub2(0x3f803f80u, fr));
          const uint32_t pp = ((iy + up) * 12 + ix) * 0x10001u + (fr >= 0x3f000000u ? 1u : 0x10000u);
          ent[m] = ((pp * 64 + ((pp << 3) & 0x300030u)) ^ ((lane >> 4) * 0x100010u)) | up;
          coefs(__shfl_sync(0xffffffffu, fn, lane >> 2), cf[m * 4], cf[m * 4 + 1]);
          coefs(__shfl_sync(0xffffffffu, fn, (lane >> 2) + 8), cf[m * 4 + 2], cf[m * 4 + 3]);
        }
        need = __reduce_or_sync(0xffffffffu, need);
        asm volatile("{\n.reg .pred p;\nsetp.ne.u32 p, %0, 0;\nbarrier.red.popc.u32 %0, %1, 128, p;\n}\n" : "+r"(out) : "r"(1 + wg) : "memory");
        out = __shfl_sync(0xffffffffu, out, 0);
        TSE(0);
        if (!out) {
          uint32_t C[2][4][8], A[2][8];
#pragma unroll
          for (int i = 0; i < 64; i++) C[0][0][i] = 0;
          auto fetch = [&](uint32_t (*c)[8], int m, uint32_t slice) {
            const uint32_t a0 = (ent[m] & 0xfff0u) + slice, a1 = (ent[m] >> 16) + slice, dy = 768 - (ent[m] & 1) * 1536;
#pragma unroll
            for (int h = 0; h < 2; h++) {
              ldsm4(c[0] + h * 4, a0 ^ (h * 32));
              ldsm4_if(c[1] + h * 4, a1 ^ (h * 32), need & (1 << (m * 3)));
              ldsm4_if(c[2] + h * 4, (a0 ^ (h * 32) ^ 32) + dy, need & (2 << (m * 3)));
              ldsm4_if(c[3] + h * 4, (a1 ^ (h * 32) ^ 32) + dy, need & (4 << (m * 3)));
            }
          };
#pragma unroll 1
          for (int sl = 0; sl < 3; sl++) {
            const uint32_t slice = win + sl * GSLICE;
            const uint64_t bd = bd0 + sl * (6 * SLOT >> 4);
            mbar_wait(gxb + sl * 8, r & 1);
            fetch(C[0], 0, slice);
#pragma unroll
            for (int m = 0; m < 9; m++) {
              if (m < 8) fetch(C[~m & 1], m + 1, slice);
              if (m % 3 == 0) mbar_wait(bars + (B_G + sl * 3 + m / 3) * 8);
              if (m >= 2) wgmma_wait<1>();
#pragma unroll
              for (int i = 0; i < 8; i++)
                A[m & 1][i] = blend(cf[m * 4 + (i & 1) * 2], cf[m * 4 + (i & 1) * 2 + 1], C[m & 1][0][i], C[m & 1][1][i], C[m & 1][2][i], C[m & 1][3][i]);
              wgmma_fence();
              wgmma_rs(acc, A[m & 1], bd + m / 3 * (2 * SLOT >> 4) + m % 3 * 192, m ? 1 : sl);
              wgmma_rs(acc, A[m & 1] + 4, bd + (m / 3 * 2 + 1) * (SLOT >> 4) + m % 3 * 192);
              wgmma_commit();
            }
            wgmma_wait<0>();
          }
        } else {
#pragma unroll 1
          for (int i = 0; i < 12; i++) mbar_wait(i < 9 ? bars + (B_G + i) * 8 : gxb + (i - 9) * 8, i < 9 ? 0 : r & 1);
          const uint32_t scratch = win + warp * 3072 + lane * 16;
#pragma unroll 1
          for (int m = 0; m < 9; m++) {
            const int ki = (m * 11) >> 5;
            const uint32_t pos = clip2(hadd2(pack2((float)(ph + ki - 1), (float)(pw + m - ki * 3 - 1)), __ldg(op + m)));
            const int gy = (int)bf16lo(pos), gx = (int)bf16hi(pos), sx = gx < IW - 1 ? 12 : 0, sy = gy < IH - 1 ? IW * 12 : 0;
            const uint4* pc = x + (gy * IW + gx) * 12 + (lane >> 4);
            uint32_t q0, q1, V[6][4][4], A[6][4];
            coefs(frac2(pos), q0, q1);
#pragma unroll
            for (int k = 0; k < 6; k++)
#pragma unroll
              for (int c = 0; c < 4; c++) ldg128(V[k][c], pc + k * 2 + (c & 1) * sx + (c >> 1) * sy);
#pragma unroll
            for (int k = 0; k < 6; k++) {
#pragma unroll
              for (int i = 0; i < 4; i++) V[k][0][i] = blend(q0, q1, V[k][0][i], V[k][1][i], V[k][2][i], V[k][3][i]);
              sts128(scratch + k * 512, V[k][0]);
            }
            __syncwarp();
#pragma unroll
            for (int k = 0; k < 6; k++) ldsm4(A[k], scratch + k * 512);
            wgmma_fence();
#pragma unroll
            for (int k = 0; k < 6; k++) wgmma_rs(acc, A[k], bd0 + ((k >> 1) * 6 + ki * 2 + (k & 1)) * (SLOT >> 4) + (m - ki * 3) * 192, k ? 1 : m);
            wgmma_commit();
            wgmma_wait<0>();
          }
        }
        acc_fence(acc);
        TSE(1);
        asm volatile("bar.sync %0, 128;\n" ::"r"(1 + wg) : "memory");
#pragma unroll
        for (int jp = 0; jp < 6; jp++) stage16<4096>(acc, jp, win + warp * 1024 + (lane & 15) * 64 + ((((lane >> 4) ^ (lane >> 1)) & 3) << 4));
        proxy_fence();
        asm volatile("bar.sync %0, 128;\n" ::"r"(1 + wg) : "memory");
        if (lead) {
          tma_store(&tm.gout, win, tx, ty);
          asm volatile("cp.async.bulk.commit_group;\ncp.async.bulk.wait_group.read 0;\n" ::: "memory");
          TSE(2);
        }
      }
    }
  } else if (wid < 12) {
    asm volatile("setmaxnreg.dec.sync.aligned.u32 32;\n");
    const int tid = thread_id(), lane = tid & 31;

    const bool one = elect_one();
    if (one && cta < NI) {
#pragma unroll
      for (int i = 0; i < 4; i++) mbar_init(bars + (B_G + (wid - 8) * 4 + i) * 8, 1);
      asm volatile("fence.mbarrier_init.release.cluster;\n" ::: "memory");
    }
    if (one && cta >= NI) {
#pragma unroll
      for (int i = 0; i < 7; i++) mbar_init(bars + (B_WF + 8 + (wid - 8) * 7 + i) * 8, 1);
      if (wid == 8) mbar_init(bars + B_WF * 8, 12);
      mbar_init(bars + (B_UR + wid - 8) * 8, 1);
      asm volatile("fence.mbarrier_init.release.cluster;\n" ::: "memory");
    }
    asm volatile("bar.arrive 3, 256;\n" ::: "memory");
    asm volatile("bar.sync 0, 512;\n" ::: "memory");
    if (cta >= NI) {
      mbar_wait(bars + (B_WF + 1) * 8);
#pragma unroll 1
      for (int t = tid; t < 1152; t += 384) {
        uint32_t g[3][4];
        const uint32_t src = sbase + u_src(t);
#pragma unroll
        for (int k = 0; k < 3; k++) lds128(g[k], src + k * 2 * SLOT);
        u_math16(g, sbase + u_dst(t));
      }
      proxy_fence();
      __syncwarp();
      arrive_if(one ? bars + B_WF * 8 : 0u);
      uint32_t a[4], d[1][6][2];
#pragma unroll
      for (int j = 0; j < 4; j++) a[j] = swz(sbase + SM_V + j * PLANE + ((tid & 127) >> 3) * 64, lane >> 1) + (lane & 1) * 8;
      const bool bot = y0 == 216;
      uint32_t off = 0;
#pragma unroll 1
      for (int u = 0; u < 6; u++) {
        const uint32_t a5 = bot && ((u ^ ry) & 1) ? a[0] : a[1], o34 = u & 1 ? 0 : 4 * PLANE;
        mbar_wait(bars + (B_XF + u) * 8);
#pragma unroll 1
        for (int i = 0; i < ((u & 3) == (wid & 3) ? 3 : 2); i += i ? 1 : 3 - ((SH >> (u * 4)) & 3)) {
          const uint32_t h = off + (i < 2 ? i * 1024 : 4096 - (wid & 2) * 256);
          v_load(d[0], a, a5, i == 2 && (lane & 16 || (x0 == 160 && lane >= 8)) ? h - (lane >> 3) * 64 : h);
          v_store(d[0], a, 4 * PLANE - o34, o34, h, i == 2 && lane >= 16 ? -1 : 0);
        }
        proxy_fence();
        __syncwarp();
        arrive_if(one ? bars + (B_XR + u) * 8 : 0u);
        off += UNIT + ((u ^ wid) & 1 ? -256 : 256);
      }
    }
  } else {
    asm volatile("setmaxnreg.dec.sync.aligned.u32 32;\n");
    const int tid = thread_id(), lane = tid & 31;
    const bool one = elect_one();
    if (wid != 12) {
      if (one) {
        if (cta >= NI) {
          if (wid == 13) {
#pragma unroll
            for (int i = 0; i < 6; i++) mbar_init(bars + (B_XR + i) * 8, 8);
          } else if (wid == 15) {
#pragma unroll
            for (int i = 2; i < 6; i++) mbar_init(bars + (B_XF + i) * 8, 1);
          }
        } else {
#pragma unroll
          for (int i = 0; i < 3; i++) mbar_init(bars + (B_WF + 1 + (wid - 13) * 3 + i) * 8, 1);
          if (wid < 15) mbar_init(bars + (wid == 13 ? B_WE : B_WF) * 8, wid == 13 ? 8 : 1);
          mbar_init(bars + (B_XF + wid - 13) * 8, 1);
        }
        if (wid == 14) {
#pragma unroll
          for (int i = 0; i < 8; i++) mbar_init(bars + (B_ST + i) * 8, 4);
#pragma unroll
          for (int i = B_OF; i <= B_OK; i++) mbar_init(bars + i * 8, i != B_OS ? 1 : cta < NI ? 8 : 2);
          if (cta >= NI) mbar_init(bars + B_CR * 8, 1);
          sts32(bars + O_CNT, 0);
        }
        asm volatile("fence.mbarrier_init.release.cluster;\n" ::: "memory");
      }
      asm volatile("bar.arrive 3, 256;\n" ::: "memory");
      asm volatile("bar.sync 0, 512;\n" ::: "memory");
      if (cta >= 48 && cta < NI) {
        if (wid == 15 && one) asm volatile("red.relaxed.gpu.global.add.u32 [%0], 1;\n" ::"l"(tm.scr->ready + 6) : "memory");
      } else {
        uint32_t epoch = 0;
        if (cta >= NI && wid < 15) {
          const uint32_t lim = (pack2((float)max(y0, 34) - 1.5f, (float)max(x0, 34) - 1.5f) & 0x7f807f80u) - 0x04000400u;
          uint32_t big = 0;
          mbar_wait(bars + B_OF * 8);
#pragma unroll 1
          for (int i0 = 0; i0 < 18; i0 += 6) {
            uint32_t v[6][4];
#pragma unroll
            for (int i = 0; i < 6; i++) lds128(v[i], sbase + SM_OFF + (tid - 416) * 16 + (i0 + i) * 1024);
            __nv_bfloat162 mx = as_bf2(0u), mn = as_bf2(0u);
#pragma unroll
            for (int i = 0; i < 6 * 2; i++) {
              mx = __hmax2_nan(__hmax2_nan(mx, as_bf2(v[i >> 1][(i & 1) * 2])), as_bf2(v[i >> 1][(i & 1) * 2 + 1]));
              mn = __hmin2_nan(__hmin2_nan(mn, as_bf2(v[i >> 1][(i & 1) * 2])), as_bf2(v[i >> 1][(i & 1) * 2 + 1]));
            }
            big |= __hblt2(__hmax2_nan(mx, __hneg2(mn)), as_bf2(lim)) ? 0u : 1u << i0;
          }
          __syncwarp();
          arrive_if(one ? bars + B_OS * 8 : 0u);
          if (wid == 13) {
            mbar_wait(bars + B_OS * 8);
            mbar_wait(bars + (B_WF + X5W) * 8);
            if (one) {
              mbar_expect_tx(bars + (B_XF + 5) * 8, UNIT);
              tma_load_3d(sbase + SM_V + 5 * UNIT, &tm.x, bars + (B_XF + 5) * 8, 64, x0 - 1, y0 + (~ry & 1) * 4 - 1);
            }
          }
#pragma unroll 1
          for (uint32_t who; (who = __ballot_sync(0xffffffffu, big)) != 0;) {
            const int src = __ffs(who) - 1;
            const uint32_t b = __reduce_or_sync(0xffffffffu, lane == src ? big : 0u);
            if (lane == src) big &= big - 1;
            const uint32_t wi = ((wid - 13) * 32 + src + (__ffs(b) - 1 + (lane >> 2)) * 64) * 4 + (lane & 3), id = (wi * 7282) >> 16, tap = wi - id * 9;
            const int ki = (tap * 11) >> 5, h = y0 + (id >> 6), w = x0 + (id & 63);
            mbar_wait(bars + B_EP * 8);
            epoch = lds32(bars + O_EPO);
            if (lds32(bars + O_CNT) > MAXEX) big = 0;
            if (lane < 24 && h >= 34 && w >= 34) {
              const uint32_t gp = pack2((float)(h + ki - 1), (float)(w + (int)tap - ki * 3 - 1));
              const uint32_t pos = clip2(hadd2(gp, __ldg(offs + (h * IW + w) * 9 + tap)));
              if (pos != hmin2(gp, 0x435f435fu)) {
                const uint32_t i = count_up(bars + O_CNT);
                if (i < MAXEX)
                  sts32(bars + O_LST + i * 4, id | (request(tm.scr, min(atomicAdd(tm.scr->ready + 8 + ((epoch >> 7) & 1), 1u) + EARLY, QUEUE), pos, h, w, tap) << 16));
              }
            }
            __syncwarp();
          }
          if (wid == 14) asm volatile("bar.arrive 7, 64;\n" ::: "memory");
        }
        if (wid == 13) {
          uint32_t m[2] = {}, cnt = 0;
          mbar_wait(bars + B_EP * 8);
          epoch = lds32(bars + O_EPO);
          if (cta >= NI ? x0 == 32 || y0 == 32 : g0 == 32) {
#pragma unroll 1
            for (uint32_t spin = 0;; spin++) {
              ld_pair(m, tm.scr->mail[cta] + min(lane, MAXEX));
              const uint32_t have = __ballot_sync(0xffffffffu, m[1] == epoch);
              cnt = __reduce_max_sync(0xffffffffu, lane == MAXEX ? m[0] : 0u);
              if ((have >> MAXEX) && (cnt > MAXEX || !(~have & ((1u << cnt) - 1)))) break;
              if (spin > (1u << 22)) __trap();
            }
          }
          if (cta >= NI) asm volatile("bar.sync 7, 64;\n" ::: "memory");
          else mbar_wait(bars + B_OS * 8);
          if (one) asm volatile("red.relaxed.gpu.global.add.u32 [%0], 1;\n" ::"l"(tm.scr->ready + 6) : "memory");
          const uint32_t own = lds32(bars + O_CNT);
          if (own && lane >= cnt) m[0] = lds32(bars + O_LST + ((lane - cnt) & 15) * 4);
          cnt += own;
          if (cnt > MAXEX || __any_sync(0xffffffffu, lane < cnt && m[0] >> 16 == QUEUE)) cnt = FAILED;
          const uint32_t id = lane < cnt ? m[0] & 511 : 512;
          const uint32_t rows = cnt == FAILED ? FAILED : __reduce_or_sync(0xffffffffu, lane < cnt ? 1u << (id >> (cta < NI ? 7 : 6)) : 0u);
          __syncwarp();
          if (lane < 16) sts32(bars + O_LST + lane * 4, id);
          if (one) sts32(bars + O_VER, rows);
          __syncwarp();
          arrive_if(one ? bars + B_OK * 8 : 0u);
          TSE(0);
          if (cnt) {
            const uint32_t z[4] = {};
#pragma unroll
            for (int k = 0; k < 6; k++) sts128(bars + O_COR + k * 512 + lane * 16, z);
            __syncwarp();
          }
#pragma unroll 1
          for (uint32_t got = 0; got < cnt && cnt != FAILED; got += 4) {
            const uint32_t i = min(got + (lane >> 3), cnt - 1);
            const uint2* r = tm.scr->res[__shfl_sync(0xffffffffu, m[0], i) >> 16] + (lane & 7);
            uint32_t v[12];
#pragma unroll 1
            for (uint32_t spin = 0;; spin++) {
              uint32_t miss = 0;
#pragma unroll
              for (int k = 0; k < 6; k++) ld_pair(v + k * 2, r + k * 8);
#pragma unroll
              for (int k = 0; k < 6; k++) miss |= v[k * 2 + 1] ^ epoch;
              if (__all_sync(0xffffffffu, !miss)) break;
              if (spin > (1u << 22)) __trap();
            }
#pragma unroll
            for (int k = 0; k < 6; k++)
              sts32(swz(bars + O_COR + (k >> 1) * 1024 + i * 64, (k & 1) * 2 + ((lane >> 2) & 1)) + (lane & 3) * 4, v[k * 2]);
          }
          proxy_fence();
          __syncwarp();
          arrive_if(one ? bars + B_CR * 8 : 0u);
#pragma unroll 1
          for (int i = cnt && cnt != FAILED ? -1 : 4; i < 4; i++) {
            const int t = (i >> 1) & 1, r = i & 1, row = cta < NI ? i : ((t ^ ry) & 1) * 4 + 2 - r;
            if (i >= 0 && !((rows >> row) & 1)) continue;
            const uint32_t base = cta < NI ? sbase + (i & 1) * 3 * SLOT : sbase + SM_X + (2 + r * 2) * UNIT + t * 21504;
            const uint32_t pitch = cta < NI ? 8192 : 4096;
            patch(bars + (i < 0 ? B_OK : B_ST + (cta < NI ? i : t) * 4) * 8, i < 0 ? lane ? 512 : 0 : id - (row << (cta < NI ? 7 : 6)),
                  cta < NI ? 128 : 64, base, pitch, bars, i < 0 ? 12 : lane);
            if (one && i >= 0) {
              if (cta < NI) {
                tma_store(&tm.bout[band], base, g0, i * 16);
              } else {
#pragma unroll
                for (int k = 0; k < 3; k++) tma_store3(&tm.out, base + k * pitch, k * 32, x0, y0 + row);
              }
            }
          }
          if (one) asm volatile("cp.async.bulk.commit_group;\ncp.async.bulk.wait_group.read 0;\n" ::: "memory");
          TSE(2);
        } else {
          if (wid == 15) {
            auto poll = [&]() {
              uint32_t v;
              asm volatile("ld.acquire.gpu.global.u32 %0, [%1];\n" : "=r"(v) : "l"(tm.scr->ready + min(lane, 6)) : "memory");
              return v;
            };
            const uint32_t epoch = (__reduce_max_sync(0xffffffffu, lane == 6 ? poll() : 0u) & ~127u) + 128;
            if (one) sts32(bars + O_EPO, epoch);
            arrive_if(one ? bars + B_EP * 8 : 0u);
            if (cta >= NI) {
              uint32_t seen = 0;
              wait_until(tstart, POLLT);
#pragma unroll 1
              for (uint32_t spin = 0; seen != 7; spin++) {
                const uint32_t now = __ballot_sync(0xffffffffu, poll() == epoch) & ~seen & 7;
                if (now) {
                  asm volatile("fence.proxy.async.global;\n" ::: "memory");
                  arrive_if((now >> lane) & 1 ? bars + (B_UR + lane) * 8 : 0u);
                  seen |= now;
                }
                if (spin > (1u << 22)) __trap();
              }
            }
          }
          asm volatile("prefetch.tensormap [%0];\n" ::"l"(reinterpret_cast<uint64_t>(cta < NI ? &tm.bout[band] : &tm.out)) : "memory");
          const int t = wid & 1;
          mbar_wait(bars + B_OK * 8);
          const int r0 = cta < NI ? t : ((t ^ ry) & 1) * 4;
          uint32_t skip = __shfl_sync(0xffffffffu, lds32(bars + O_VER), 0);
          skip = (skip == FAILED || cta < NI ? skip : skip & 0x66) >> r0;
          if (cta < NI) {
            mbar_wait(bars + (B_ST + t * 4) * 8);
            if (one && !(skip & 1)) tma_store(&tm.bout[band], sbase + t * 3 * SLOT, g0, t * 16);
          } else {
#pragma unroll
            for (int r = 0; r < 4; r++) {
              const uint32_t base = r < 2 ? sbase + SM_X + (2 + r * 2) * UNIT + t * 21504 : sbase + SM_V + t * (UNIT + 4 * PLANE) + (r - 2) * PLANE;
              if (r != 1) mbar_wait(bars + (B_ST + t * 4 + max(r - 1, 0)) * 8);
              if (r == PDR) mbar_wait(bars + (B_UR + 3) * 8);
              if (!((skip >> ((2 - r) & 3)) & 1)) {
#pragma unroll
                for (int k = 0; k < 3; k++)
                  if (one) tma_store3(&tm.out, base + k * (r < 2 ? 4096 : 2 * UNIT), k * 32, x0, y0 + r0 + ((2 - r) & 3));
              }
            }
          }
          if (one) asm volatile("cp.async.bulk.commit_group;\ncp.async.bulk.wait_group.read 0;\n" ::: "memory");
          TSE(2);
        }
      }
    } else if (cta < NI) {
        auto load_x = [&](int s) {
          mbar_expect_tx(bars + (B_XF + s) * 8, YSLICE);
          tma_load_3d(sbase + SM_YX + s * YSLICE, &tm.bx[band], bars + (B_XF + s) * 8, s * 32, g0 - 1, -2);
        };
        auto load_w = [&](int p) {
          const int s = (p * 11) >> 5, b = p - s * 3;
          mbar_expect_tx(bars + (B_WF + p) * 8, 2 * SLOT);
#pragma unroll
          for (int h = 0; h < 2; h++)
            tma_load_5d(sbase + (p * 2 + h) * SLOT, &tm.bw[band], bars + (B_WF + p) * 8, s * 32 + h * 16, band ? 0 : b, band ? b : 0);
        };
        asm volatile("bar.arrive 0, 512;\n" ::: "memory");
        asm volatile("bar.sync 3, 256;\n" ::: "memory");
        if (one && cta >= 48) {
#pragma unroll 1
          for (int sl = 0; sl < 3; sl++) {
            wait_until(tstart, CSLEEP + sl * GDT);
#pragma unroll
            for (int wg = 0; wg < 2; wg++) {
              mbar_expect_tx(bars + (B_G + 9 + wg * 3 + sl) * 8, GSLICE);
              tma_load_3d(sbase + SM_GX + (wg * 3 + sl) * GSLICE, &tm.gx, bars + (B_G + 9 + wg * 3 + sl) * 8, sl * 32,
                          (cta & 2) * 4 + ((cta >> 2 ^ wg) & 1) * 16 - 2, (cta & 1) * 8 + wg * 16 - 2);
            }
#pragma unroll 1
            for (int i = 0; i < 6; i++) {
              if (!(i & 1)) mbar_expect_tx(bars + (B_G + sl * 3 + (i >> 1)) * 8, 2 * SLOT);
              tma_load_5d(sbase + (sl * 6 + i) * SLOT, &tm.bw[1], bars + (B_G + sl * 3 + (i >> 1)) * 8, sl * 32 + (i & 1) * 16, 0, i >> 1);
            }
          }
        }
        if (one && cta < 48) {
          arrive_if(bars + (B_WF + 9) * 8);
#pragma unroll 1
          for (int p = 0; p < 9; p++) {
            wait_until(tstart, p > 4 ? YWT + 3 * YWDT + (p - 4) * YWD2 : p ? YWT + (p - 1) * YWDT : BSLEEP);
            if (p == 0 || p == 3 || p == 6) load_x(p >> 1 & 1 ? (p >> 2) + 1 : 0);
            if (p == 8) mbar_wait(bars + B_WE * 8);
            load_w(p);
          }
        }
    } else {
        auto load_x = [&](int u) {
          mbar_expect_tx(bars + (B_XF + u) * 8, UNIT);
          tma_load_3d(sbase + SM_V + u * UNIT, &tm.x, bars + (B_XF + u) * 8, (u >> 1) * 32, x0 - 1, y0 + ((u ^ ry) & 1) * 4 - 1);
        };
        asm volatile("bar.sync 3, 256;\n" ::: "memory");
        if (lane < 28) mbar_expect_tx(bars + (B_WF + 8 + lane) * 8, lane == 16 ? 3 * SLOT : lane == 17 || lane == 18 ? 0 : SLOT);
        if (smem_u32(smem) != sbase) __trap();
#pragma unroll 1
        for (int xu = 2; xu <= 3; xu++) {
          wait_until(tstart, XT1 + (xu - 1) * XDT);
          if (xu == 3) mbar_wait(bars + B_WF * 8);
          if (one) load_x(xu);
          if (xu == OFFAT && one) {
            mbar_expect_tx(bars + B_OF * 8, 2 * SLOT);
            tma_load_3d(sbase + SM_OFF, &tm.off, bars + B_OF * 8, 0, x0 * 9 / 32, y0);
          }
        }
        const uint4* src = tm.scr->u;
        uint32_t fb = bars + (B_WF + 8) * 8;
#pragma unroll 1
        for (int q = 0; q < 6; q++) {
          mbar_wait(bars + (B_UR + (q >> 1)) * 8);
          if (q == 4) {
            if (one) bulk_load<3 * SLOT>(sbase + SM_X, src, fb);
            if (one) bulk_load<SLOT>(sbase + SM_X + 2 * UNIT + 12288, src + 3 * 576, fb + 24);
            src += 4 * 576;
            fb += 32;
          }
          const uint32_t dst = sbase + SM_W + (q & 1) * 4 * SLOT, id = 8 + (q & 1) * 4;
#pragma unroll
          for (int k = 0; k < 4; k++) {
            asm volatile("bar.sync %0, 96;\n" ::"r"(id + k) : "memory");
            if (one) bulk_load<SLOT>(dst + k * SLOT, src + k * 576, fb + k * 8);
            if (k == 3 && q == 5 && one) arrive_if(bars + (B_UR + 3) * 8);
          }
          if (q == X4Q && one) load_x(4);
          src += 4 * 576;
          fb += 32;
        }
    }
  }
}

typedef CUresult (*EncodeTiledFn)(CUtensorMap*, CUtensorMapDataType, cuuint32_t, void*, const cuuint64_t*,
                                  const cuuint64_t*, const cuuint32_t*, const cuuint32_t*, CUtensorMapInterleave,
                                  CUtensorMapSwizzle, CUtensorMapL2promotion, CUtensorMapFloatOOBfill);

}

extern "C" void kernel_launch(void* const* d_in, const int* in_sizes, int n_in, void* d_out, int out_size) {
  static EncodeTiledFn encode = nullptr;
  static Scratch* scratch = nullptr;
  if (!encode) {
    void* fn = nullptr;
    cudaDriverEntryPointQueryResult qres;
    cudaGetDriverEntryPoint("cuTensorMapEncodeTiled", &fn, cudaEnableDefault, &qres);
    encode = (EncodeTiledFn)fn;
    cudaGetSymbolAddress((void**)&scratch, g_scratch);
    cudaFuncSetAttribute(dcn_kernel, cudaFuncAttributeMaxDynamicSharedMemorySize, SMEM_BYTES);
  }
  uint32_t* tsp = nullptr;
  Maps tm;
  tm.scr = scratch;
  auto make = [&](CUtensorMap* m, void* p, int rank, const cuuint64_t* dims, const cuuint64_t* strides, const cuuint32_t* box, bool swizzle) {
    const cuuint32_t es[5] = {1, 1, 1, 1, 1};
    encode(m, CU_TENSOR_MAP_DATA_TYPE_BFLOAT16, rank, p, dims, strides, box, es, CU_TENSOR_MAP_INTERLEAVE_NONE,
           swizzle ? CU_TENSOR_MAP_SWIZZLE_64B : CU_TENSOR_MAP_SWIZZLE_NONE, CU_TENSOR_MAP_L2_PROMOTION_NONE,
           CU_TENSOR_MAP_FLOAT_OOB_FILL_NONE);
  };
  const cuuint64_t PX = IC * 2, ROW = IW * IC * 2, TAP = IC * IC * 2;
  for (int t = 0; t < 2; t++) {
    const cuuint64_t dims[3] = {IC, IW, IH}, odims[4] = {32, IW, IH, 3}, strides[3] = {t ? ROW : PX, t ? PX : ROW, 64};
    const cuuint32_t xb[3] = {32, 66, 6}, ob[3] = {32, 64, 1}, bxb[3] = {32, 10, 36}, bob[4] = {32, 8, 16, 3};
    if (!t) make(&tm.x, d_in[0], 3, dims, strides, xb, true);
    if (!t) make(&tm.out, d_out, 3, dims, strides, ob, true);
    const cuuint32_t gxb[3] = {32, 12, 12}, gob[4] = {32, 8, 8, 3};
    if (!t) make(&tm.gx, d_in[0], 3, dims, strides, gxb, true);
    if (!t) make(&tm.gout, d_out, 4, odims, strides, gob, true);
    make(&tm.bx[t], d_in[0], 3, dims, strides, bxb, true);
    make(&tm.bout[t], d_out, 4, odims, strides, bob, true);
    const cuuint64_t wdims[5] = {32, IC, 3, 3, 3}, wstrides[4] = {PX, 64, TAP, 3 * TAP};
    const cuuint32_t wb[5] = {32, 16, 3, t ? 3u : 1u, t ? 1u : 3u};
    make(&tm.bw[t], d_in[2], 5, wdims, wstrides, wb, true);
  }
  {
    const cuuint64_t dims[3] = {64, 144, 9}, strides[2] = {128, TAP};
    const cuuint32_t box[3] = {64, 48, 9};
    make(&tm.w, d_in[2], 3, dims, strides, box, false);
    const cuuint64_t cdims[4] = {64, 144, 3, 3}, cstrides[3] = {128, TAP, 3 * TAP};
    const cuuint32_t cbox[4] = {64, 24, 1, 3};
    make(&tm.wc, d_in[2], 4, cdims, cstrides, cbox, false);
    const cuuint64_t odims[3] = {64, 63, IH}, ostrides[2] = {128, IW * 36};
    const cuuint32_t obox[3] = {64, 18, 8};
    make(&tm.off, d_in[1], 3, odims, ostrides, obox, false);
    const cuuint32_t cb[3] = {64, 1, IH};
    make(&tm.col, d_in[1], 3, odims, ostrides, cb, false);
  }
  dcn_kernel<<<GRID, NTHREADS, SMEM_BYTES>>>((const uint4*)d_in[0], (const uint32_t*)d_in[1], tsp, 0u, tm);
}
```

```cpp
#include <cuda_runtime.h>
#include <cuda.h>
#include <cuda_bf16.h>
#include <stdint.h>

namespace {

constexpr int IH = 224, IW = 224, IC = 96;
constexpr int GRID = 132, NTHREADS = 512;
constexpr int NI = 60;
constexpr int SLOT = 9216;
constexpr int SMEM_BYTES = 232448;
constexpr int PLANE = 66 * 64, UNIT = 6 * PLANE;
constexpr int SM_V = 256, SM_X = SM_V + 2 * PLANE, SM_W = 36 * PLANE + 512, SM_BAR = SM_W + 8 * SLOT;
constexpr int SM_RAW = SM_V + 3 * UNIT, SM_OFF = SM_V + 6 * UNIT - 2 * SLOT;
constexpr int YSLICE = 36 * 10 * 64, SM_YX = 16 * SLOT, SM_YT = SM_YX + 3 * YSLICE;
constexpr int GSLICE = 144 * 64, SM_GX = 18 * SLOT;
constexpr int B_WF = 0, B_WE = 36, B_XF = 60, B_XR = 66, B_ST = 72, B_UR = 80, B_OF = 84, B_OS = 85, B_EP = 86, B_OK = 87, B_G = 88, B_CR = 103;
constexpr int O_CNT = 832, O_VER = 848, O_EPO = 852, O_LST = 864, O_COR = 1024;
constexpr int MAXEX = 16, EARLY = 128, QUEUE = 192;
constexpr uint32_t FAILED = 0xffff;
constexpr uint32_t X1T = 1800, XT2 = 3400, XT3 = 4300, POLLT = 4600;
constexpr uint32_t BSLEEP = 2200, YWT = 3800, YWDT = 1100, YWD2 = 800, YPAUSE_NS = 1200;
constexpr uint32_t CSLEEP = 1500, GDT = 3500;

struct Scratch {
  uint4 u[16 * SLOT / 16];
  uint4 w[12 * SLOT / 16];
  uint32_t ready[32];
  uint2 req[QUEUE];
  uint2 res[QUEUE][48];
  uint2 mail[GRID][32];
};
__device__ __align__(128) Scratch g_scratch;

#define TSE(i)

__device__ __forceinline__ float bf16lo(uint32_t v) { return __uint_as_float(v << 16); }
__device__ __forceinline__ float bf16hi(uint32_t v) { return __uint_as_float(v & 0xffff0000u); }
__device__ __forceinline__ uint32_t smem_u32(const void* p) { return (uint32_t)__cvta_generic_to_shared(p); }
__device__ __forceinline__ void mbar_init(uint32_t bar, uint32_t count) {
  asm volatile("mbarrier.init.shared::cta.b64 [%0], %1;\n" ::"r"(bar), "r"(count) : "memory");
}
__device__ __forceinline__ void mbar_expect_tx(uint32_t bar, uint32_t bytes) {
  asm volatile("mbarrier.arrive.expect_tx.shared::cta.b64 _, [%0], %1;\n" ::"r"(bar), "r"(bytes) : "memory");
}
__device__ __forceinline__ void mbar_wait(uint32_t bar, uint32_t parity = 0) {
  uint32_t done;
#pragma unroll 1
  for (uint32_t spin = 0; spin < (1u << 22); spin++) {
    asm volatile(
        "{\n.reg .pred p;\n"
        "mbarrier.try_wait.parity.shared::cta.b64 p, [%1], %2;\n"
        "selp.u32 %0, 1, 0, p;\n}\n"
        : "=r"(done)
        : "r"(bar), "r"(parity)
        : "memory");
    if (done) return;
  }
  __trap();
}
__device__ __forceinline__ uint32_t clock32() {
  uint32_t c;
  asm volatile("mov.u32 %0, %%clock;\n" : "=r"(c)::"memory");
  return c;
}
__device__ __forceinline__ void wait_until(uint32_t t0, uint32_t dt) {
  while (clock32() - t0 < dt) __nanosleep(50);
}
__device__ __forceinline__ void tma_load_3d(uint32_t dst, const CUtensorMap* tm, uint32_t bar, int c0, int c1, int c2) {
  asm volatile(
      "cp.async.bulk.tensor.3d.shared::cluster.global.mbarrier::complete_tx::bytes [%0], [%1, {%3, %4, %5}], [%2];\n" ::"r"(dst),
      "l"(reinterpret_cast<uint64_t>(tm)), "r"(bar), "r"(c0), "r"(c1), "r"(c2)
      : "memory");
}
__device__ __forceinline__ void tma_load_5d(uint32_t dst, const CUtensorMap* tm, uint32_t bar, int c, int kj, int ki) {
  asm volatile(
      "cp.async.bulk.tensor.5d.shared::cluster.global.mbarrier::complete_tx::bytes [%0], [%1, {%3, %4, %3, %5, %6}], [%2];\n" ::"r"(dst),
      "l"(reinterpret_cast<uint64_t>(tm)), "r"(bar), "r"(0), "r"(c), "r"(kj), "r"(ki)
      : "memory");
}
__device__ __forceinline__ void tma_load_4d(uint32_t dst, const CUtensorMap* tm, uint32_t bar, int c1, int c2, int c3) {
  asm volatile(
      "cp.async.bulk.tensor.4d.shared::cluster.global.mbarrier::complete_tx::bytes [%0], [%1, {%3, %4, %5, %6}], [%2];\n" ::"r"(dst),
      "l"(reinterpret_cast<uint64_t>(tm)), "r"(bar), "r"(0), "r"(c1), "r"(c2), "r"(c3)
      : "memory");
}
template <int BYTES>
__device__ __forceinline__ void bulk_load(uint32_t dst, const void* src, uint32_t bar) {
  asm volatile("cp.async.bulk.shared::cluster.global.mbarrier::complete_tx::bytes [%0], [%1], %3, [%2];\n" ::"r"(dst), "l"(src),
               "r"(bar), "n"(BYTES)
               : "memory");
}
__device__ __forceinline__ void tma_store3(const CUtensorMap* tm, uint32_t src, int c0, int c1, int c2) {
  asm volatile("cp.async.bulk.tensor.3d.global.shared::cta.bulk_group [%0, {%2, %3, %4}], [%1];\n" ::"l"(
                   reinterpret_cast<uint64_t>(tm)),
               "r"(src), "r"(c0), "r"(c1), "r"(c2)
               : "memory");
}
__device__ __forceinline__ void tma_store(const CUtensorMap* tm, uint32_t src, int c1, int c2) {
  asm volatile("cp.async.bulk.tensor.4d.global.shared::cta.bulk_group [%0, {%2, %3, %4, %2}], [%1];\n" ::"l"(
                   reinterpret_cast<uint64_t>(tm)),
               "r"(src), "r"(0), "r"(c1), "r"(c2)
               : "memory");
}
__device__ __forceinline__ uint64_t w_desc(uint32_t saddr) {
  return (uint64_t)((saddr & 0x3FFFF) >> 4) | ((uint64_t)(1024 >> 4) << 16) | ((uint64_t)(512 >> 4) << 32) | ((uint64_t)2 << 62);
}
__device__ __forceinline__ uint64_t a_desc(uint32_t saddr) {
  return (uint64_t)((saddr & 0x3FFFF) >> 4) | ((uint64_t)1 << 16) | ((uint64_t)(512 >> 4) << 32) | ((uint64_t)2 << 62);
}
#define ACC_OPERANDS(c, d)                                                                                        \
  c(d[0]), c(d[1]), c(d[2]), c(d[3]), c(d[4]), c(d[5]), c(d[6]), c(d[7]), c(d[8]),      \
      c(d[9]), c(d[10]), c(d[11]), c(d[12]), c(d[13]), c(d[14]), c(d[15]), c(d[16]),       \
      c(d[17]), c(d[18]), c(d[19]), c(d[20]), c(d[21]), c(d[22]), c(d[23]), c(d[24]),      \
      c(d[25]), c(d[26]), c(d[27]), c(d[28]), c(d[29]), c(d[30]), c(d[31]), c(d[32]),      \
      c(d[33]), c(d[34]), c(d[35]), c(d[36]), c(d[37]), c(d[38]), c(d[39]), c(d[40]),      \
      c(d[41]), c(d[42]), c(d[43]), c(d[44]), c(d[45]), c(d[46]), c(d[47])
#define ACC_LIST                                                                   \
  "{%0, %1, %2, %3, %4, %5, %6, %7, %8, %9, %10, %11, %12, %13, %14, %15, "        \
  "%16, %17, %18, %19, %20, %21, %22, %23, %24, %25, %26, %27, %28, %29, %30, %31, " \
  "%32, %33, %34, %35, %36, %37, %38, %39, %40, %41, %42, %43, %44, %45, %46, %47}, "
__device__ __forceinline__ void wgmma_ss(float* d, uint64_t adesc, uint64_t bdesc, int accumulate = 1) {
  asm volatile(
      "{\n.reg .pred p;\nsetp.ne.b32 p, %50, 0;\n"
      "wgmma.mma_async.sync.aligned.m64n96k16.f32.bf16.bf16 " ACC_LIST "%48, %49, p, 1, 1, 0, 1;\n}\n"
      : ACC_OPERANDS("+f", d)
      : "l"(adesc), "l"(bdesc), "r"(accumulate));
}
__device__ __forceinline__ void wgmma_fence() { asm volatile("wgmma.fence.sync.aligned;\n" ::: "memory"); }
__device__ __forceinline__ void wgmma_commit() { asm volatile("wgmma.commit_group.sync.aligned;\n" ::: "memory"); }
template <int N>
__device__ __forceinline__ void wgmma_wait() { asm volatile("wgmma.wait_group.sync.aligned %0;\n" ::"n"(N) : "memory"); }
__device__ __forceinline__ void acc_fence(float* d) {
#pragma unroll
  for (int i = 0; i < 48; i++) asm volatile("" : "+f"(d[i])::"memory");
}
__device__ __forceinline__ void arrive_if(uint32_t bar) {
  asm volatile("{\n.reg .pred p;\nsetp.ne.u32 p, %0, 0;\n@p mbarrier.arrive.shared::cluster.b64 _, [%0];\n}\n" ::"r"(bar) : "memory");
}
__device__ __forceinline__ void lds128(uint32_t* v, uint32_t addr) {
  asm volatile("ld.shared.v4.b32 {%0, %1, %2, %3}, [%4];\n" : "=r"(v[0]), "=r"(v[1]), "=r"(v[2]), "=r"(v[3]) : "r"(addr) : "memory");
}
__device__ __forceinline__ void sts128(uint32_t addr, const uint32_t* v) {
  asm volatile("st.shared.v4.b32 [%0], {%1, %2, %3, %4};\n" ::"r"(addr), "r"(v[0]), "r"(v[1]), "r"(v[2]), "r"(v[3]) : "memory");
}
__device__ __forceinline__ __nv_bfloat162 as_bf2(uint32_t v) { return *reinterpret_cast<__nv_bfloat162*>(&v); }
__device__ __forceinline__ uint32_t as_u32(__nv_bfloat162 v) { return *reinterpret_cast<uint32_t*>(&v); }
__device__ __forceinline__ uint32_t hfma2(uint32_t a, uint32_t b, uint32_t c) { return as_u32(__hfma2(as_bf2(a), as_bf2(b), as_bf2(c))); }
__device__ __forceinline__ uint32_t pack2(float a, float b) { return as_u32(__floats2bfloat162_rn(a, b)); }
__device__ __forceinline__ bool elect_one() {
  uint32_t r;
  asm volatile("{\n.reg .pred p;\nelect.sync _|p, 0xffffffff;\nselp.u32 %0, 1, 0, p;\n}\n" : "=r"(r));
  return r != 0;
}
__device__ __forceinline__ void wgmma_rs(float* d, const uint32_t* a, uint64_t bdesc, int accumulate = 1) {
  asm volatile(
      "{\n.reg .pred p;\nsetp.ne.b32 p, %53, 0;\n"
      "wgmma.mma_async.sync.aligned.m64n96k16.f32.bf16.bf16 " ACC_LIST "{%48, %49, %50, %51}, %52, p, 1, 1, 1;\n}\n"
      : ACC_OPERANDS("+f", d)
      : "r"(a[0]), "r"(a[1]), "r"(a[2]), "r"(a[3]), "l"(bdesc), "r"(accumulate));
}
__device__ __forceinline__ void ldsm4(uint32_t* r, uint32_t addr) {
  asm volatile("ldmatrix.sync.aligned.m8n8.x4.shared.b16 {%0, %1, %2, %3}, [%4];\n"
               : "=r"(r[0]), "=r"(r[1]), "=r"(r[2]), "=r"(r[3])
               : "r"(addr)
               : "memory");
}
__device__ __forceinline__ void lds64(uint32_t* v, uint32_t addr) {
  asm volatile("ld.shared.v2.b32 {%0, %1}, [%2];\n" : "=r"(v[0]), "=r"(v[1]) : "r"(addr) : "memory");
}
__device__ __forceinline__ void sts32(uint32_t addr, uint32_t v) {
  asm volatile("st.shared.u32 [%0], %1;\n" ::"r"(addr), "r"(v) : "memory");
}
__device__ __forceinline__ uint32_t hadd2(uint32_t a, uint32_t b) { return as_u32(__hadd2(as_bf2(a), as_bf2(b))); }
__device__ __forceinline__ uint32_t hsub2(uint32_t a, uint32_t b) { return as_u32(__hsub2(as_bf2(a), as_bf2(b))); }
__device__ __forceinline__ uint32_t hmin2(uint32_t a, uint32_t b) { return as_u32(__hmin2(as_bf2(a), as_bf2(b))); }
__device__ __forceinline__ uint32_t hmax2(uint32_t a, uint32_t b) { return as_u32(__hmax2(as_bf2(a), as_bf2(b))); }
__device__ __forceinline__ uint32_t hfma2_lo(uint32_t w, uint32_t a, uint32_t c) {
  return as_u32(__hfma2(__low2bfloat162(as_bf2(w)), as_bf2(a), as_bf2(c)));
}
__device__ __forceinline__ uint32_t hfma2_hi(uint32_t w, uint32_t a, uint32_t c) {
  return as_u32(__hfma2(__high2bfloat162(as_bf2(w)), as_bf2(a), as_bf2(c)));
}
__device__ __forceinline__ uint32_t prmt(uint32_t a, uint32_t b, uint32_t sel) {
  uint32_t r;
  asm("prmt.b32 %0, %1, %2, %3;\n" : "=r"(r) : "r"(a), "r"(b), "r"(sel));
  return r;
}
__device__ __forceinline__ constexpr uint32_t tap_delta(int a, int b) {
  return (a == 0 ? 0xbf80u : a == 1 ? 0u : 0x3f80u) | (b == 0 ? 0xbf800000u : b == 1 ? 0u : 0x3f800000u);
}
__device__ __forceinline__ int thread_id() {
  int t;
  asm volatile("mov.u32 %0, %%tid.x;\n" : "=r"(t));
  return t;
}
__device__ __forceinline__ void proxy_fence() { asm volatile("fence.proxy.async.shared::cta;\n" ::: "memory"); }
template <int PITCH>
__device__ __forceinline__ void stage16(const float* acc, int jp, uint32_t stg) {
  uint32_t pk[4];
#pragma unroll
  for (int i = 0; i < 4; i++) pk[i] = pack2(acc[jp * 8 + i * 2], acc[jp * 8 + i * 2 + 1]);
  asm volatile("stmatrix.sync.aligned.m8n8.x4.shared.b16 [%0], {%1, %2, %3, %4};\n" ::"r"((stg ^ ((jp & 1) * 32)) + (jp >> 1) * PITCH),
               "r"(pk[0]), "r"(pk[1]), "r"(pk[2]), "r"(pk[3])
               : "memory");
}
__device__ __forceinline__ uint32_t swz(uint32_t a, uint32_t chunk) { return a | (((chunk ^ (a >> 7)) & 3) << 4); }

__device__ __forceinline__ void v_load(uint32_t (*d)[2], const uint32_t* a, uint32_t a5, uint32_t off) {
#pragma unroll
  for (int j = 0; j < 6; j++) lds64(d[j], (j == 5 ? a5 : a[j & 3]) + (j >> 2) * 4 * PLANE + off);
}
__device__ __forceinline__ void sts64_if(uint32_t addr, uint32_t a, uint32_t b, int on) {
  asm volatile("{\n.reg .pred p;\nsetp.ge.s32 p, %3, 0;\n@p st.shared.v2.b32 [%0], {%1, %2};\n}\n" ::"r"(addr), "r"(a), "r"(b), "r"(on) : "memory");
}
__device__ __forceinline__ void v_store(uint32_t (*d)[2], const uint32_t* a, uint32_t o05, uint32_t o34, uint32_t off, int on = 0) {
#pragma unroll
  for (int i = 0; i < 2; i++)
    asm volatile(
        "{\n.reg .b32 p, q, r, c;\n"
        "add.rn.bf16x2 %0, %0, %4;\n"
        "add.rn.bf16x2 %5, %5, %1;\n"
        "mov.b32 c, 0xc080c080;\n"
        "fma.rn.bf16x2 p, c, %2, %4;\n"
        "fma.rn.bf16x2 q, c, %1, %3;\n"
        "mov.b32 c, 0xc088c088;\n"
        "fma.rn.bf16x2 %0, c, %2, %0;\n"
        "fma.rn.bf16x2 %5, c, %3, %5;\n"
        "mov.b32 c, 0xbe80be80;\n"
        "fma.rn.bf16x2 r, c, %2, %4;\n"
        "fma.rn.bf16x2 %3, c, %1, %3;\n"
        "mov.b32 c, 0x3f003f00;\n"
        "fma.rn.bf16x2 %1, c, q, p;\n"
        "mov.b32 c, 0xbf00bf00;\n"
        "fma.rn.bf16x2 %2, c, q, p;\n"
        "mov.b32 c, 0x40004000;\n"
        "fma.rn.bf16x2 %4, c, %3, r;\n"
        "mov.b32 c, 0xc000c000;\n"
        "fma.rn.bf16x2 %3, c, %3, r;\n}\n"
        : "+r"(d[0][i]), "+r"(d[1][i]), "+r"(d[2][i]), "+r"(d[3][i]), "+r"(d[4][i]), "+r"(d[5][i]));
  sts64_if(a[0] + o05 + off, d[0][0], d[0][1], on);
  sts64_if(a[1] + o05 + off, d[5][0], d[5][1], on);
  sts64_if(a[2] + off, d[1][0], d[1][1], on);
  sts64_if(a[3] + off, d[2][0], d[2][1], on);
  sts64_if(a[0] + o34 + off, d[4][0], d[4][1], on);
  sts64_if(a[1] + o34 + off, d[3][0], d[3][1], on);
}
__device__ __forceinline__ void u_math16(const uint32_t (*g)[4], uint32_t dst) {
#pragma unroll
  for (int h = 0; h < 2; h++) {
    uint32_t u[2][4];
#pragma unroll
    for (int i = 0; i < 4; i++) {
      const uint32_t s = hfma2(0x3e803e80u, g[2 - h * 2][i], g[h * 2][i]);
      u[0][i] = hfma2(0x3f003f00u, g[1][i], s);
      u[1][i] = hfma2(0xbf00bf00u, g[1][i], s);
    }
    sts128(dst + h * 2 * SLOT, u[0]);
    sts128(dst + (h * 2 + 1) * SLOT, u[1]);
  }
}
__device__ __forceinline__ uint32_t u_src(int t) {
  const int c = t >= 576, q = t - c * 576, b = q >> 6, kj = (b * 11) >> 5;
  return SM_RAW + c * 3072 + kj * (6144 - 192) + b * 64 + ((q >> 2) & 15) * 192 + (q & 3) * 16;
}
__device__ __forceinline__ uint32_t u_dst(int t) { return SM_W + (t >= 576 ? 3 * SLOT : 0) + (t ^ ((t >> 3) & 3)) * 16; }

__device__ __forceinline__ void ldg128(uint32_t* v, const uint4* p) {
  asm volatile("ld.global.nc.v4.b32 {%0, %1, %2, %3}, [%4];\n" : "=r"(v[0]), "=r"(v[1]), "=r"(v[2]), "=r"(v[3]) : "l"(p));
}
__device__ __forceinline__ uint32_t lds32(uint32_t addr) {
  uint32_t v;
  asm volatile("ld.shared.u32 %0, [%1];\n" : "=r"(v) : "r"(addr) : "memory");
  return v;
}
__device__ __forceinline__ void ldsm4_if(uint32_t* r, uint32_t addr, uint32_t on) {
  asm volatile(
      "{\n.reg .pred p;\nsetp.ne.u32 p, %5, 0;\n"
      "@p ldmatrix.sync.aligned.m8n8.x4.shared.b16 {%0, %1, %2, %3}, [%4];\n}\n"
      : "+r"(r[0]), "+r"(r[1]), "+r"(r[2]), "+r"(r[3])
      : "r"(addr), "r"(on)
      : "memory");
}
__device__ __forceinline__ uint32_t hmul2_lo(uint32_t w, uint32_t a) { return as_u32(__hmul2(__low2bfloat162(as_bf2(w)), as_bf2(a))); }
__device__ __forceinline__ uint32_t clip2(uint32_t p) { return hmin2(hmax2(p, 0u), 0x435f435fu); }
__device__ __forceinline__ uint32_t frac2(uint32_t pos) {
  const float py = bf16lo(pos), px = bf16hi(pos);
  return __byte_perm(__float_as_uint(py - floorf(py)), __float_as_uint(px - floorf(px)), 0x7632);
}
__device__ __forceinline__ void coefs(uint32_t w, uint32_t& p0, uint32_t& p1) {
  const uint32_t o = hsub2(0x3f803f80u, w), xa = __byte_perm(o, w, 0x7632);
  p0 = hmul2_lo(o, xa);
  p1 = hmul2_lo(w, xa);
}
__device__ __forceinline__ uint32_t blend(uint32_t p0, uint32_t p1, uint32_t t, uint32_t g, uint32_t h, uint32_t k) {
  return hfma2_hi(p1, k, hfma2_lo(p1, h, hfma2_hi(p0, g, hmul2_lo(p0, t))));
}
__device__ __forceinline__ void st_pair(uint2* p, uint32_t a, uint32_t b) {
  asm volatile("{\n.reg .b64 v;\nmov.b64 v, {%1, %2};\nst.relaxed.gpu.global.b64 [%0], v;\n}\n" ::"l"(p), "r"(a), "r"(b) : "memory");
}
__device__ __forceinline__ void ld_pair(uint32_t* v, const uint2* p) {
  asm volatile("{\n.reg .b64 v;\nld.relaxed.gpu.global.b64 v, [%2];\nmov.b64 {%0, %1}, v;\n}\n" : "=r"(v[0]), "=r"(v[1]) : "l"(p) : "memory");
}
__device__ __forceinline__ uint32_t request(Scratch* scr, uint32_t slot, uint32_t pos, int h, int w, int tap) {
  if (slot < QUEUE) st_pair(scr->req + slot, pos, 0x80000000u | (h << 12) | (w << 4) | tap);
  return slot;
}
__device__ __forceinline__ uint32_t count_up(uint32_t addr) {
  uint32_t i;
  asm volatile("atom.shared.add.u32 %0, [%1], 1;\n" : "=r"(i) : "r"(addr) : "memory");
  return i;
}
__device__ __forceinline__ void patch(uint32_t bar, uint32_t id, uint32_t n, uint32_t base, uint32_t pitch, uint32_t ctl, int lane) {
  uint32_t todo = __ballot_sync(0xffffffffu, id < n);
#pragma unroll 1
  do {
    const int i0 = __ffs(todo) - 1;
    todo &= todo - 1;
    const uint32_t p0 = __reduce_max_sync(0xffffffffu, lane == i0 ? id : 0u), other = todo & __ballot_sync(0xffffffffu, id != p0);
    const int i1 = __ffs(other) - 1;
    todo &= ~(other & -other);
    const uint32_t p1 = __reduce_max_sync(0xffffffffu, lane == i1 ? id : 0u);
    const bool on = (lane & 15) < 12 && (lane < 16 || other);
    const uint32_t a = on ? swz(base + ((lane >> 2) & 3) * pitch + (lane < 16 ? p0 : p1) * 64, lane) : ctl + O_LST + 64;
    uint32_t v[4], c[4];
    lds128(c, swz(ctl + O_COR + ((lane >> 2) & 3) * 1024 + (lane < 16 ? i0 : i1) * 64, lane));
    mbar_wait(bar);
    lds128(v, a);
#pragma unroll
    for (int k = 0; k < 4; k++) v[k] = hadd2(v[k], c[k]);
    sts128(a, v);
    __syncwarp();
  } while (todo);
  proxy_fence();
  __syncwarp();
}

__host__ __device__ __forceinline__ int role_of(int b) {
  const int k = b >> 1;
  return b & 1 ? (k < 4 ? k + 56 : k < 60 ? k - 4 : k + 66) : k + 60;
}

struct Maps {
  Scratch* scr;
  CUtensorMap x, w, wc, out, off, col, gx, gout;
  CUtensorMap bx[2], bw[2], bout[2];
};

__global__ void __launch_bounds__(NTHREADS, 1)
dcn_kernel(const uint4* __restrict__ x, const uint32_t* __restrict__ offs, uint32_t* tsp,
           const uint32_t never, const __grid_constant__ Maps tm) {
  extern __shared__ __align__(1024) uint8_t smem[];
  constexpr uint32_t sbase = 1024;
  constexpr uint32_t bars = sbase + SM_BAR;
  const uint32_t tstart = clock32();
  const int tid = thread_id();
  const int wid = __shfl_sync(0xffffffffu, tid >> 5, 0);
  const bool first = wid == 12 && (!(blockIdx.x & 1) || blockIdx.x >= 120);
  if (first && elect_one()) {
    mbar_init(bars + (B_WF + 1) * 8, 1);
    tma_load_3d(sbase + SM_RAW, &tm.w, bars + (B_WF + 1) * 8, 0, 0, 0);
  }
  const int cta = role_of(blockIdx.x);
  const int lane = tid & 31;
  const int ri = cta - NI, ry = ri / 3, x0 = 32 + (ri - ry * 3) * 64, y0 = 32 + ry * 8;
  const int band = cta >= 24, g0 = 32 + (cta - band * 24) * 8;
  if (first) {
    const bool one = elect_one();
    if (one) {
      mbar_init(bars + B_XF * 8, 1);
      mbar_init(bars + (B_XF + 1) * 8, 1);
      asm volatile("fence.mbarrier_init.release.cluster;\n" ::: "memory");
      tma_load_3d(sbase + SM_V, &tm.x, bars + B_XF * 8, 0, x0 - 1, y0 + (ry & 1) * 4 - 1);
      mbar_expect_tx(bars + (B_WF + 1) * 8, 6 * SLOT);
      mbar_expect_tx(bars + B_XF * 8, UNIT);
      mbar_expect_tx(bars + (B_XF + 1) * 8, UNIT);
    }
    asm volatile("bar.arrive 0, 512;\n" ::: "memory");
    if (one) {
      while (clock32() - tstart < X1T) {}
      tma_load_3d(sbase + SM_V + UNIT, &tm.x, bars + (B_XF + 1) * 8, 0, x0 - 1, y0 + (~ry & 1) * 4 - 1);
    }
  }
  if (wid == 12 && cta >= NI - 4 && cta < NI) {
    if (elect_one()) {
#pragma unroll
      for (int c = 0; c < 5; c++) mbar_init(bars + c * 8, 1);
      asm volatile("fence.mbarrier_init.release.cluster;\n" ::: "memory");
    }
    asm volatile("bar.arrive 0, 512;\n" ::: "memory");
    if (elect_one()) {
      if (cta < NI - 1) {
#pragma unroll
        for (int c = 0; c < 4; c++) {
          mbar_expect_tx(bars + c * 8, SLOT);
          tma_load_4d(sbase + (18 + c) * SLOT, &tm.wc, bars + c * 8, (c + 2) * 24, cta - (NI - 4), 0);
        }
      } else {
        mbar_expect_tx(bars + 3 * 8, 28672 + 16128);
        tma_load_3d(sbase + 18 * SLOT, &tm.col, bars + 3 * 8, 0, 9, 0);
        bulk_load<16128>(sbase + 18 * SLOT + 28672, offs + 32 * IW * 9, bars + 3 * 8);

      }
    }
  }
  if (cta >= NI - 4 && cta < NI) {
    const int kj = cta - (NI - 4);
    if (wid != 12) asm volatile("bar.sync 0, 512;\n" ::: "memory");
    auto get_epoch = [&]() {
      uint32_t e;
      asm volatile("ld.relaxed.gpu.global.u32 %0, [%1];\n" : "=r"(e) : "l"(tm.scr->ready + (kj == 3 ? 3 : 2)) : "memory");
      return (e & ~127u) + 128;
    };
    uint32_t epoch;
    auto load_w = [&]() {
      mbar_expect_tx(bars + 4 * 8, 18 * SLOT);
#pragma unroll
      for (int sl = 0; sl < 3; sl++) tma_load_3d(sbase + sl * 6 * SLOT, &tm.w, bars + 4 * 8, 0, sl * 48, 0);
    };
    if (kj == 3) {
      constexpr uint32_t src = sbase + 18 * SLOT, lst = src + 28672 + 16128;
      uint32_t big = 0;
      epoch = get_epoch();
      if (tid < GRID) sts32(bars + 64 + tid * 4, 0);
      asm volatile("bar.sync 1, 512;\n" ::: "memory");
      if (tid == 0) load_w();
      mbar_wait(bars + 3 * 8);
#pragma unroll
      for (int i = 0; i < 6; i++) {
        const uint32_t p = tid + i * 512;
        uint32_t v[4];
        lds128(v, src + p * 16);
        const uint32_t lim = i == 0 && tid < 256 ? 0x42804080u : i >= 3 && (p - 1792 < 72 || p - 2296 < 72) ? 0x40804280u : 0x42804280u;
        uint32_t over = 0;
#pragma unroll
        for (int k = 0; k < 4; k++) over |= (v[k] & 0x7fff7fffu) + lim;
        if ((over & 0x80008000u) && (p < 1792 ? (tid & 7) < 5 : p < 2800)) big |= 1u << i;
      }
#pragma unroll 1
      for (; big; big &= big - 1) {
        const uint32_t i = count_up(bars + 64 + 57 * 4);
        if (i < 1024) sts32(lst + i * 4, tid + (__ffs(big) - 1) * 512);
      }
      __syncwarp();
      asm volatile("bar.sync 1, %0;\n" ::"r"(512 + (epoch & never)) : "memory");
      const uint32_t n = lds32(bars + 64 + 57 * 4);
      if (n > 1024 && tid < GRID && (tid < 56 || tid >= NI)) sts32(bars + 64 + tid * 4, FAILED);
#pragma unroll 1
      for (uint32_t c = tid; c < n * 4 && n <= 1024; c += 512) {
        const uint32_t wq = lds32(lst + (c & ~3u)) * 4 + (c & 3), col = wq < 7168;
        const uint32_t wi = col ? wq & 31 : wq - 7168, px = (wi * 7282) >> 16, tap = wi - px * 9;
        const int eh = col ? wq >> 5 : 32 + (px >= 224), ew = col ? 32 + px : px >= 224 ? px - 224 : px, ki = (tap * 11) >> 5;
        const uint32_t gp = pack2((float)(eh + ki - 1), (float)(ew + (int)tap - ki * 3 - 1));
        const uint32_t pos = clip2(hadd2(gp, lds32(src + wq * 4)));
        const uint32_t d = __byte_perm(hsub2(pos, hmin2(gp, 0x435f435fu)), 0, ew < 32 ? 0x1032 : 0x3210) & 0x7fff7fffu;
        if (d <= (min(eh, ew) < 32 ? 0x3f80u : 0u) || (col && (px >= 2 || eh >> 1 == 16))) continue;
        const int client = eh < 32 ? 0 : ew < 32 ? 24 : NI + ((eh - 32) >> 3) * 3 + ((ew - 32) >> 6);
        const uint32_t i = count_up(bars + 64 + client * 4);
        if (i >= MAXEX) continue;
        const uint32_t slot = count_up(bars + 64 + 56 * 4);
        const uint32_t id = eh < 32 ? eh * 8 + ew - 32 : ew < 32 ? ew * 8 + eh - 32 : (eh & 7) * 64 + ((ew - 32) & 63);
        st_pair(tm.scr->mail[client] + i, id | (request(tm.scr, slot < EARLY ? slot : QUEUE, pos, eh, ew, tap) << 16), epoch);
      }
      __syncwarp();
      asm volatile("bar.sync 1, %0;\n" ::"r"(512 + (epoch & never)) : "memory");
      if (tid < GRID) st_pair(tm.scr->mail[tid] + MAXEX, lds32(bars + 64 + tid * 4), epoch);
      if (tid == 0) {
        tm.scr->ready[3] = epoch;
        tm.scr->ready[8 + ((epoch >> 7) & 1 ^ 1)] = 0;
      }
      TSE(2);
    } else if (wid < 12) {
      const int half = wid >= 6, q = tid - half * 192;
      const uint32_t lin = (q >> 6) * 64 + ((q >> 2) & 15) * 192 + (q & 3) * 16;
      const int e = kj * 192 + (q ^ ((q >> 3) & 3));
#pragma unroll 1
      for (int c = half - 2; c < 4; c += 2) {
        uint4 g[3], u[4];
        if (c >= 0) mbar_wait(bars + c * 8);
#pragma unroll
        for (int k = 0; k < 3; k++) lds128(&g[k].x, sbase + (18 + c) * SLOT + k * 3072 + lin);
#pragma unroll
        for (int i = 0; i < 4; i++) {
            const uint32_t s = hfma2(0x3e803e80u, (&g[2].x)[i], (&g[0].x)[i]), t = hfma2(0x3e803e80u, (&g[0].x)[i], (&g[2].x)[i]);
            (&u[0].x)[i] = hfma2(0x3f003f00u, (&g[1].x)[i], s);
            (&u[1].x)[i] = hfma2(0xbf00bf00u, (&g[1].x)[i], s);
            (&u[2].x)[i] = hfma2(0x3f003f00u, (&g[1].x)[i], t);
            (&u[3].x)[i] = hfma2(0xbf00bf00u, (&g[1].x)[i], t);
        }
        if (c >= 2) asm volatile("bar.sync 2, 416;\n" ::: "memory");
#pragma unroll
        for (int k = 0; k < 4; k++)
          asm volatile("{\n.reg .pred p;\nsetp.ge.s32 p, %5, 0;\n@p st.global.v4.b32 [%0], {%1, %2, %3, %4};\n}\n" ::"l"(tm.scr->u + (c * 4 + k) * 576 + e),
                       "r"(u[k].x), "r"(u[k].y), "r"(u[k].z), "r"(u[k].w), "r"(c) : "memory");
        if (c >= 0) asm volatile("bar.arrive 1, 416;\n" ::: "memory");
      }
      epoch = get_epoch();
      if (!half) {
        mbar_wait(bars + 4 * 8);
#pragma unroll 6
        for (int c = 0; c < 12; c++) {
          uint4 v;
          lds128(&v.x, sbase + (c % 6 >> 1) * 6 * SLOT + (c / 6 * 6 + kj) * 6144 + (c & 1) * 3072 + lin);
          tm.scr->w[c * 576 + e] = v;
        }
      }
      asm volatile("bar.arrive 3, %0;\n" ::"r"(512 + (epoch & never)) : "memory");
    } else if (wid == 12) {
      epoch = get_epoch();
#pragma unroll 1
      for (int r = 0; r < 3; r++) {
        asm volatile("bar.sync %0, %1;\n" ::"r"(r < 2 ? 1 : 3), "r"((r < 2 ? 416 : 512) + (epoch & never)) : "memory");
        if (elect_one()) {
          asm volatile("red.release.gpu.global.add.u32 [%0], %1;\n" ::"l"(tm.scr->ready + r), "r"(kj ? 32 : 64) : "memory");
          if (r == 1) load_w();
        }
        __syncwarp();
        if (r == 0) asm volatile("bar.arrive 2, 416;\n" ::: "memory");
      }
    } else {
      epoch = get_epoch();
      asm volatile("bar.arrive 3, %0;\n" ::"r"(512 + (epoch & never)) : "memory");
    }
    const uint32_t dl = sbase + 18 * SLOT + 4 * 12288 + wid * 384;
#pragma unroll 1
    for (int slot = (wid == 12 ? 15 : wid > 12 ? 15 - wid : 14 - wid) * 4 + (kj ^ 3); slot < QUEUE; slot += 64) {
      uint2 rq;
#pragma unroll 1
      for (uint32_t spin = 0;; spin++) {
        uint32_t done[2];
        ld_pair(&rq.x, tm.scr->req + slot);
        if (slot < EARLY) {
          ld_pair(done, tm.scr->mail[56] + MAXEX);
          if (rq.y || (done[1] == epoch && slot >= done[0])) break;
        } else {
          asm volatile("ld.acquire.gpu.global.u32 %0, [%1];\n" : "=r"(done[1]) : "l"(tm.scr->ready + 6) : "memory");
          if (rq.y) break;
          if (done[1] == epoch) {
            asm volatile("ld.relaxed.gpu.global.u32 %0, [%1];\n" : "=r"(done[0]) : "l"(tm.scr->ready + 8 + ((epoch >> 7) & 1)) : "memory");
            if (slot - EARLY >= done[0]) break;
          }
        }
        if (spin > (1u << 22)) __trap();
        __nanosleep(100);
      }
      if (!rq.y) continue;
      __syncwarp();
      if (lane == 0) tm.scr->req[slot] = make_uint2(0, 0);
      const int tap = rq.y & 15, ki = (tap * 11) >> 5, gy = (int)bf16lo(rq.x), gx = (int)bf16hi(rq.x);
      const int cy = min(max((int)((rq.y >> 12) & 255) + ki - 1, 0), IH - 1), cx = min(max((int)((rq.y >> 4) & 255) + tap - ki * 3 - 1, 0), IW - 1);
      if (lane < 24) {
        const uint2* pc = reinterpret_cast<const uint2*>(x) + lane;
        const int p = (gy * IW + gx) * 24, sx = gx < IW - 1 ? 24 : 0, sy = gy < IH - 1 ? IW * 24 : 0;
        const uint2 v0 = __ldg(pc + p), v1 = __ldg(pc + p + sx), v2 = __ldg(pc + p + sy), v3 = __ldg(pc + p + sy + sx);
        const uint2 c = __ldg(pc + (cy * IW + cx) * 24);
        uint32_t q0, q1;
        coefs(frac2(rq.x), q0, q1);
        const uint32_t d0 = hsub2(blend(q0, q1, v0.x, v1.x, v2.x, v3.x), c.x), d1 = hsub2(blend(q0, q1, v0.y, v1.y, v2.y, v3.y), c.y);
        const uint32_t dd[4] = {__byte_perm(d0, 0, 0x1010), __byte_perm(d0, 0, 0x3232), __byte_perm(d1, 0, 0x1010), __byte_perm(d1, 0, 0x3232)};
        sts128(dl + lane * 16, dd);
      }
      __syncwarp();
      mbar_wait(bars + 4 * 8);
      float sum[8] = {};
      const int l24 = min(lane, 23);
#pragma unroll 1
      for (int b = 0; b < 6; b++) {
        uint32_t part[4] = {};
#pragma unroll
        for (int i = 0; i < 8; i++) {
          uint32_t wv[4];
          lds128(wv, sbase + (b >> 1) * 6 * SLOT + tap * 6144 + (b & 1) * 3072 + i * 384 + l24 * 16);
          const uint32_t d = lds32(dl + (b * 16 + i * 2 + (l24 >= 12)) * 4);
#pragma unroll
          for (int k = 0; k < 4; k++) part[k] = hfma2(d, wv[k], part[k]);
        }
#pragma unroll
        for (int k = 0; k < 4; k++) {
          sum[k * 2] += bf16lo(part[k]);
          sum[k * 2 + 1] += bf16hi(part[k]);
        }
      }
#pragma unroll
      for (int k = 0; k < 8; k++) sum[k] += __shfl_down_sync(0xffffffffu, sum[k], 12);
      if (lane < 12) {
#pragma unroll
        for (int k = 0; k < 4; k++)
          st_pair(tm.scr->res[slot] + lane * 4 + k, pack2(sum[k * 2], sum[k * 2 + 1]), epoch);
      }
      TSE(1);
    }
    mbar_wait(bars + 4 * 8);
  } else if (wid < 8) {
    const int wg = wid >> 2, warp = wid & 3;
    if (cta < 48) {
    const int f = wid * 4 + (lane >> 3), g = g0 + (lane & 7);
    uint32_t cf[36];
    wait_until(tstart, BSLEEP);
    {
      const uint32_t* op = offs + (band ? g * IW + f : f * IW + g) * 9;
#pragma unroll
      for (int a = 0; a < 3; a++)
#pragma unroll
        for (int b = 0; b < 3; b++) cf[a * 3 + b] = __ldg(op + (band ? b * 3 + a : a * 3 + b));
    }
    asm volatile("bar.sync 0, 512;\n" ::: "memory");
    {
      const uint32_t base = pack2((float)f, (float)g), sel = band ? 0x1032u : 0x3210u;
      const uint32_t tab = sbase + SM_YT + wid * 1152;
      uint32_t bad = 0;
#pragma unroll
      for (int a = 0; a < 3; a++)
#pragma unroll
        for (int b = 0; b < 3; b++) {
          const uint32_t gp = hadd2(base, tap_delta(a, b));
          const uint32_t pos = clip2(hadd2(gp, __byte_perm(cf[a * 3 + b], 0, sel)));
          uint32_t d = hsub2(pos, hmin2(gp, 0x435f435fu));
          if ((d & 0x7fff7fffu) > 0x3f80u) {
            bad = 1;
            d = a == 0 && f == 0 ? 0x3f80u : 0u;
          }
          sts32(tab + (lane & 7) * 144 + (b * 12 + (lane >> 3) * 3 + a) * 4, (d << 16) | (d & 0x8000u ? 0x3210u : 0x7654u));
        }
      if (bad && g >= 34) sts32(bars + O_CNT, FAILED);
      __syncwarp();
      arrive_if(lane == 0 ? bars + B_OS * 8 : 0u);
      asm volatile("setmaxnreg.inc.sync.aligned.u32 224;\n");
      __syncwarp();
#pragma unroll
      for (int i = 0; i < 9; i++) lds128(cf + i * 4, tab + (lane >> 2) * 144 + i * 16);
    }
    uint32_t xa[3];
#pragma unroll
    for (int b = 0; b < 3; b++)
      xa[b] = swz(sbase + SM_YX + ((wid * 4 + (lane >> 4)) * 10 + min((lane & 7) + b, IW - g0)) * 64, (lane >> 3) & 1);
    float acc[2][48];
    uint32_t X[2][16], A[2][12];
    auto fetch = [&](uint32_t* r, uint32_t a) {
#pragma unroll
      for (int i = 0; i < 4; i++) ldsm4(r + i * 4, (a ^ ((i & 1) * 32)) + i * 1280);
    };
    uint64_t bd = w_desc(sbase);
    uint32_t wf = bars + B_WF * 8;
    mbar_wait(bars + B_XF * 8);
    TSE(0);
    fetch(X[0], xa[0]);
    mbar_wait(wf);
#pragma unroll 1
    for (int s = 0; s < 3; s++) {
#pragma unroll
      for (int n = 0; n < 6; n++) {
        const int b = n >> 1;
        if (n == 5) {
          mbar_wait(bars + (B_XF + min(s + 1, 2)) * 8);
#pragma unroll
          for (int k = 0; k < 3; k++) xa[k] += s < 2 ? YSLICE : 0;
        }
        fetch(X[~n & 1], xa[(n + 1) % 6 >> 1] ^ ((~n & 1) * 32));
        const uint32_t* xr = X[n & 1];
        uint32_t D[7][2];
#pragma unroll
        for (int j = 0; j < 7; j++)
#pragma unroll
          for (int e = 0; e < 2; e++) D[j][e] = hsub2(xr[(j + 1) * 2 + e], xr[j * 2 + e]);
#pragma unroll
        for (int t = 0; t < 2; t++) {
          wgmma_wait<1>();
#pragma unroll
          for (int a = 0; a < 3; a++)
#pragma unroll
            for (int i = 0; i < 4; i++) {
              const int o = t * 2 + (i & 1), e = i >> 1, j = o + a + 1;
              const uint32_t c = cf[b * 12 + o * 3 + a];
              A[t][a * 4 + i] = hfma2_hi(c, prmt(D[j - 1][e], D[j][e], c), xr[j * 2 + e]);
            }
          wgmma_fence();
#pragma unroll
          for (int a = 0; a < 3; a++) wgmma_rs(acc[t], A[t] + a * 4, bd + n * (SLOT >> 4) + a * 192, (n | a) ? 1 : s);
          wgmma_commit();
        }
        if (n & 1) mbar_wait(wf + (b + 1) * 8);
        if (n == 1 && s == 1 && elect_one()) arrive_if(bars + B_WE * 8);
      }
      bd += 6 * SLOT >> 4;
      wf += 24;
      if (s == 1 && wg) __nanosleep(YPAUSE_NS);
    }
    TSE(1);
    const int lane = thread_id() & 31;
    const uint32_t stg = sbase + wg * 3 * SLOT + (wid & 3) * 2048 + (lane & 15) * 64 + ((((lane >> 4) ^ (lane >> 1)) & 3) << 4);
    wgmma_wait<1>();
    acc_fence(acc[0]);
#pragma unroll
    for (int jp = 0; jp < 6; jp++) stage16<8192>(acc[0], jp, stg);
    wgmma_wait<0>();
    acc_fence(acc[1]);
#pragma unroll
    for (int jp = 0; jp < 6; jp++) stage16<8192>(acc[1], jp, stg + 1024);
    proxy_fence();
    __syncwarp();
    arrive_if(lane == 0 ? bars + (B_ST + wg * 4) * 8 : 0u);
    } else if (cta < NI) {
      asm volatile("bar.sync 0, 512;\n" ::: "memory");
      asm volatile("setmaxnreg.inc.sync.aligned.u32 224;\n");
    } else {
    {
      uint32_t g[3][3][4], src[3], dst[3];
#pragma unroll
      for (int r = 0; r < 3; r++) {
        src[r] = sbase + u_src(tid + r * 384);
        dst[r] = sbase + u_dst(tid + r * 384);
      }
      asm volatile("bar.sync 0, 512;\n" ::: "memory");
      mbar_wait(bars + (B_WF + 1) * 8);
#pragma unroll
      for (int r = 0; r < 3; r++) {
#pragma unroll
        for (int k = 0; k < 3; k++) lds128(g[r][k], src[r] + k * 2 * SLOT);
      }
#pragma unroll
      for (int r = 0; r < 3; r++) u_math16(g[r], dst[r]);
      proxy_fence();
      __syncwarp();
      arrive_if(lane == 0 ? bars + B_WF * 8 : 0u);
    }
    asm volatile("setmaxnreg.inc.sync.aligned.u32 224;\n");
    float m[4][48];
    const uint32_t vb = sbase + SM_V + wg * UNIT;
    const uint64_t bd0 = w_desc(sbase + SM_W), ad12 = a_desc(vb + 2 * PLANE), ad05 = a_desc(vb + (wg ? 4 * PLANE : 0));

    const uint64_t d34 = wg ? -(2 * PLANE >> 4) : 2 * PLANE >> 4;
    uint64_t ad = ad12;
    uint32_t wf = bars + B_WF * 8, a[4];
    {
      const int t = thread_id();
#pragma unroll
      for (int j = 0; j < 4; j++) a[j] = swz(vb + j * PLANE + ((t & 127) >> 3) * 64, t >> 1) + (t & 1) * 8;
    }
#pragma unroll 1
    for (int sl = 0; sl < 3; sl++) {
      {
        uint32_t d[6][2];
        const uint32_t a5 = y0 == 216 && ((wg ^ ry) & 1) ? a[0] : a[1], o34 = wg ? 0 : 4 * PLANE;
        mbar_wait(bars + (B_XF + sl * 2 + wg) * 8);
#pragma unroll 1
        for (uint32_t o = wg ? 1024 : 2048; o < 4096; o += 1024) {
          v_load(d, a, a5, o);
          v_store(d, a, 4 * PLANE - o34, o34, o);
        }
        proxy_fence();
        __syncwarp();
        if (elect_one()) arrive_if(bars + (B_XR + sl * 2 + wg) * 8);
#pragma unroll
        for (int j = 0; j < 4; j++) asm volatile("add.u32 %0, %0, %1;\n" : "+r"(a[j]) : "n"(2 * UNIT));
        mbar_wait(wf);
        mbar_wait(bars + (B_XR + sl * 2 + wg) * 8);
        if (wg && sl == 2) asm volatile("bar.sync 6, 256;\n" ::: "memory");
      }
#pragma unroll
      for (int n = 0; n < 8; n++) {
        const int k = n & 3;
        wgmma_fence();
#pragma unroll
        for (int kj = 0; kj < 3; kj++)
          wgmma_ss(m[k], (k < 2 ? ad : ad + d34) + (k & 1) * (PLANE >> 4) + n / 4 * 2 + kj * 4, bd0 + n * (SLOT >> 4) + kj * 192, (n / 4 | kj) ? 1 : sl);
        wgmma_commit();
        if (n < 7) {
          if (sl) mbar_wait(wf + (n + 1) * 8);
          wgmma_wait<1>();
          if (warp == 0 && n) asm volatile("bar.arrive %0, 96;\n" ::"r"(7 + n) : "memory");
        }
      }
      if (sl == 2) asm volatile("bar.arrive %0, 256;\n" ::"r"(wg ? 4 : 6) : "memory");
      wgmma_wait<1>();
      if (warp == 0) asm volatile("bar.arrive 14, 96;\n" ::: "memory");
      wgmma_wait<0>();
      if (warp == 0) asm volatile("bar.arrive 15, 96;\n" ::: "memory");
      ad += 2 * UNIT >> 4;
      wf += 64;

    }
    const int lane = thread_id() & 31;
    const uint32_t stg = sbase + SM_X + 2 * UNIT + wg * 21504 + warp * 1024 + (lane & 15) * 64 + ((((lane >> 4) ^ (lane >> 1)) & 3) << 4);
    const uint32_t stb = lane == 0 ? bars + (B_ST + wg * 4) * 8 : 0u;
    auto publish = [&](int k) {
      proxy_fence();
      __syncwarp();
      arrive_if(stb ? stb + k * 8 : 0u);
    };
#pragma unroll
    for (int k = 0; k < 4; k++) acc_fence(m[k]);
    float dep = 0.f;
#pragma unroll
    for (int i0 = 0; i0 < 48; i0 += 8) {
      const float k0 = __uint_as_float((__float_as_uint(dep) & never) | 0xbf088889u);
      const float k1 = __uint_as_float((__float_as_uint(dep) & never) | 0xbf800000u);
#pragma unroll
      for (int i = i0; i < i0 + 8; i++) {
        m[0][i] *= k0;
        m[3][i] = fmaf(k1, m[3][i], m[2][i]);
        m[1][i] = fmaf(-8.0f / 15.0f, m[1][i], m[0][i]);
        m[2][i] = fmaf(-0.5f, m[3][i], m[2][i]);
        m[0][i] = fmaf(-0.5f, m[1][i], m[0][i]);
        m[1][i] = fmaf(4.0f / 15.0f, m[2][i], m[1][i]);
        m[0][i] = fmaf(4.0f / 15.0f, m[3][i], m[0][i]);
        m[2][i] = fmaf(0.25f, m[1][i], m[2][i]);
        m[3][i] = fmaf(0.25f, m[0][i], m[3][i]);
        dep = m[0][i];
        if ((i & 7) == 7) {
          stage16<4096>(m[2], i >> 3, stg);
          stage16<4096>(m[0], i >> 3, stg + 2 * UNIT);
        }
      }
    }
    publish(0);
    asm volatile("bar.sync %0, 256;\n" ::"r"(4 + wg) : "memory");
    uint32_t rows, ids[4];
    const uint64_t bdx = w_desc(sbase + SM_X);
    const uint32_t s05 = vb + (wg ? 4 * PLANE : 0) + warp * 1024 + (lane & 15) * 64;
#pragma unroll
    for (int j = 0; j < 12; j++) {
      float* acc = j < 6 ? m[1] : m[3];
      const int c = j % 6;
      const uint64_t ad = ad05 + (c >> 1) * (2 * UNIT >> 4) + (c & 1) * 2 + (j < 6 ? 0 : PLANE >> 4);
      const uint64_t bd = j < 3 ? bdx + j * (SLOT >> 4) : j == 3 ? bdx + ((2 * UNIT + 12288) >> 4) : bd0 + (j - 4) * (SLOT >> 4);
      if (j != 1 && j != 2) mbar_wait(bars + (B_WF + 24 + j) * 8);
      if (j == 5 || j == 11) {
        const uint32_t row = ((wg ^ ry) & 1) * 4 + (j == 5 ? 0 : 3), me = row * 64 + warp * 16 + (lane >> 2);
        if (__any_sync(0xffffffffu, rows != FAILED && ((rows >> row) & 1))) {
          uint32_t sel[4];
#pragma unroll
          for (int i = 0; i < 4; i++)
            sel[i] = (ids[(i >> 1) * 2] == me + (i & 1) * 8 ? 0x3f80u : 0u) | (ids[(i >> 1) * 2 + 1] == me + (i & 1) * 8 ? 0x3f800000u : 0u);
          mbar_wait(bars + B_CR * 8);
          wgmma_fence();
          wgmma_rs(acc, sel, w_desc(bars + O_COR));
        }
      }
      wgmma_fence();
#pragma unroll
      for (int kj = 0; kj < 3; kj++) wgmma_ss(acc, ad + kj * 4, bd + kj * 192);
      wgmma_commit();
      if (j == 1) {
        mbar_wait(bars + B_OK * 8);
        rows = lds32(bars + O_VER);
        lds64(ids, bars + O_LST + (lane & 3) * 8);
        lds64(ids + 2, bars + O_LST + 32 + (lane & 3) * 8);
      }
      if (j == 7) {
        wgmma_wait<2>();
        acc_fence(m[1]);
      }
      if (j >= 7 && j <= 9) {
#pragma unroll
        for (int jp = j * 2 - 14; jp < j * 2 - 12; jp++) stage16<2 * UNIT>(m[1], jp, swz(s05, lane >> 4));
      }
      if (j == 10) publish(1);
      if (j == 11 && !wg) asm volatile("bar.arrive 5, 256;\n" ::: "memory");
    }
    wgmma_wait<0>();
    acc_fence(m[3]);
    TSE(1);
#pragma unroll
    for (int jp = 0; jp < 6; jp++) stage16<2 * UNIT>(m[3], jp, swz(s05 + PLANE, lane >> 4));
    publish(2);
    }
    int rounds = 1;
    const int tid = thread_id(), lane = tid & 31;
    if (cta < 48 || cta >= NI) {
      mbar_wait(bars + B_OK * 8);
      rounds = lds32(bars + O_VER) != FAILED ? 0 : cta < 48 ? 2 : 4;
      rounds = __shfl_sync(0xffffffffu, rounds, 0);
    }
    if (rounds) {
      const bool lead = warp == 0 && elect_one();
      if (rounds > 1) {
        if (tid == 0) {
#pragma unroll
          for (int i = 0; i < 15; i++) mbar_init(bars + (B_G + i) * 8, 1);
          asm volatile("fence.mbarrier_init.release.cluster;\n" ::: "memory");
        }
        proxy_fence();
        asm volatile("bar.sync 3, 256;\n" ::: "memory");
      }
      const uint32_t win = sbase + SM_GX + wg * 3 * GSLICE, gxb = bars + (B_G + 9 + wg * 3) * 8;
      const uint64_t bd0 = w_desc(sbase);
      float acc[48];
#pragma unroll 1
      for (int r = 0; r < rounds; r++) {
        int ty, tx, bx;
        asm volatile("mov.u32 %0, %%ctaid.x;\n" : "=r"(bx));
        const int cta = role_of(bx), ry = (cta - NI) / 3, x0 = 32 + (cta - NI - ry * 3) * 64, y0 = 32 + ry * 8;
        const int band = cta >= 24, g0 = 32 + (cta - band * 24) * 8;
        if (cta >= NI) { ty = y0; tx = x0 + r * 16 + wg * 8; }
        else if (cta < 48) { ty = band ? g0 : r * 16 + wg * 8; tx = band ? r * 16 + wg * 8 : g0; }
        else { ty = (cta & 1) * 8 + wg * 16; tx = (cta & 2) * 4 + ((cta >> 2 ^ wg) & 1) * 16; }
        if (lead && rounds > 1) {
#pragma unroll 1
          for (int sl = 0; sl < 3; sl++) {
            mbar_expect_tx(gxb + sl * 8, GSLICE);
            tma_load_3d(win + sl * GSLICE, &tm.gx, gxb + sl * 8, sl * 32, tx - 2, ty - 2);
            if (r == 0) {
#pragma unroll 1
              for (int ki = 0; ki < 3; ki++) {
                if (!wg) mbar_expect_tx(bars + (B_G + sl * 3 + ki) * 8, 2 * SLOT);
                tma_load_5d(sbase + ((sl * 3 + ki) * 2 + wg) * SLOT, &tm.bw[1], bars + (B_G + sl * 3 + ki) * 8, sl * 32 + wg * 16, 0, ki);
              }
            }
          }
        }
        const int ph = ty + warp * 2 + ((lane >> 3) & 1), pw = tx + (lane & 7);
        const uint32_t* op = offs + (ph * IW + pw) * 9;
        const uint32_t base = pack2((float)ph, (float)pw);
        uint32_t ent[9], cf[36], need = 0, out = 0;
#pragma unroll
        for (int m = 0; m < 9; m++) ent[m] = __ldg(op + m);
#pragma unroll
        for (int m = 0; m < 9; m++) {
          const uint32_t pos = clip2(hadd2(hadd2(base, tap_delta(m / 3, m % 3)), ent[m])), fr = frac2(pos);
          const uint32_t iy = (int)bf16lo(pos) - (ty - 2), ix = (int)bf16hi(pos) - (tx - 2);
          out |= max(iy, ix) > 10;
          need |= ((fr >> 16 ? 1u : 0u) | (fr & 0xffffu ? 2u : 0u) | (fr >> 16 && (fr & 0xffffu) ? 4u : 0u)) << (m * 3);
          const uint32_t up = (fr & 0xffffu) >= 0x3f00u, fn = hmin2(fr, hsub2(0x3f803f80u, fr));
          const uint32_t pp = ((iy + up) * 12 + ix) * 0x10001u + (fr >= 0x3f000000u ? 1u : 0x10000u);
          ent[m] = ((pp * 64 + ((pp << 3) & 0x300030u)) ^ ((lane >> 4) * 0x100010u)) | up;
          coefs(__shfl_sync(0xffffffffu, fn, lane >> 2), cf[m * 4], cf[m * 4 + 1]);
          coefs(__shfl_sync(0xffffffffu, fn, (lane >> 2) + 8), cf[m * 4 + 2], cf[m * 4 + 3]);
        }
        need = __reduce_or_sync(0xffffffffu, need);
        asm volatile("{\n.reg .pred p;\nsetp.ne.u32 p, %0, 0;\nbarrier.red.popc.u32 %0, %1, 128, p;\n}\n" : "+r"(out) : "r"(1 + wg) : "memory");
        out = __shfl_sync(0xffffffffu, out, 0);
        TSE(0);
        if (!out) {
          uint32_t C[2][4][8], A[2][8];
#pragma unroll
          for (int i = 0; i < 64; i++) C[0][0][i] = 0;
          auto fetch = [&](uint32_t (*c)[8], int m, uint32_t slice) {
            const uint32_t a0 = (ent[m] & 0xfff0u) + slice, a1 = (ent[m] >> 16) + slice, dy = 768 - (ent[m] & 1) * 1536;
#pragma unroll
            for (int h = 0; h < 2; h++) {
              ldsm4(c[0] + h * 4, a0 ^ (h * 32));
              ldsm4_if(c[1] + h * 4, a1 ^ (h * 32), need & (1 << (m * 3)));
              ldsm4_if(c[2] + h * 4, (a0 ^ (h * 32) ^ 32) + dy, need & (2 << (m * 3)));
              ldsm4_if(c[3] + h * 4, (a1 ^ (h * 32) ^ 32) + dy, need & (4 << (m * 3)));
            }
          };
#pragma unroll 1
          for (int sl = 0; sl < 3; sl++) {
            const uint32_t slice = win + sl * GSLICE;
            const uint64_t bd = bd0 + sl * (6 * SLOT >> 4);
            mbar_wait(gxb + sl * 8, r & 1);
            fetch(C[0], 0, slice);
#pragma unroll
            for (int m = 0; m < 9; m++) {
              if (m < 8) fetch(C[~m & 1], m + 1, slice);
              if (m % 3 == 0) mbar_wait(bars + (B_G + sl * 3 + m / 3) * 8);
              if (m >= 2) wgmma_wait<1>();
#pragma unroll
              for (int i = 0; i < 8; i++)
                A[m & 1][i] = blend(cf[m * 4 + (i & 1) * 2], cf[m * 4 + (i & 1) * 2 + 1], C[m & 1][0][i], C[m & 1][1][i], C[m & 1][2][i], C[m & 1][3][i]);
              wgmma_fence();
              wgmma_rs(acc, A[m & 1], bd + m / 3 * (2 * SLOT >> 4) + m % 3 * 192, m ? 1 : sl);
              wgmma_rs(acc, A[m & 1] + 4, bd + (m / 3 * 2 + 1) * (SLOT >> 4) + m % 3 * 192);
              wgmma_commit();
            }
            wgmma_wait<0>();
          }
        } else {
#pragma unroll 1
          for (int i = 0; i < 12; i++) mbar_wait(i < 9 ? bars + (B_G + i) * 8 : gxb + (i - 9) * 8, i < 9 ? 0 : r & 1);
          const uint32_t scratch = win + warp * 3072 + lane * 16;
#pragma unroll 1
          for (int m = 0; m < 9; m++) {
            const int ki = (m * 11) >> 5;
            const uint32_t pos = clip2(hadd2(pack2((float)(ph + ki - 1), (float)(pw + m - ki * 3 - 1)), __ldg(op + m)));
            const int gy = (int)bf16lo(pos), gx = (int)bf16hi(pos), sx = gx < IW - 1 ? 12 : 0, sy = gy < IH - 1 ? IW * 12 : 0;
            const uint4* pc = x + (gy * IW + gx) * 12 + (lane >> 4);
            uint32_t q0, q1, V[6][4][4], A[6][4];
            coefs(frac2(pos), q0, q1);
#pragma unroll
            for (int k = 0; k < 6; k++)
#pragma unroll
              for (int c = 0; c < 4; c++) ldg128(V[k][c], pc + k * 2 + (c & 1) * sx + (c >> 1) * sy);
#pragma unroll
            for (int k = 0; k < 6; k++) {
#pragma unroll
              for (int i = 0; i < 4; i++) V[k][0][i] = blend(q0, q1, V[k][0][i], V[k][1][i], V[k][2][i], V[k][3][i]);
              sts128(scratch + k * 512, V[k][0]);
            }
            __syncwarp();
#pragma unroll
            for (int k = 0; k < 6; k++) ldsm4(A[k], scratch + k * 512);
            wgmma_fence();
#pragma unroll
            for (int k = 0; k < 6; k++) wgmma_rs(acc, A[k], bd0 + ((k >> 1) * 6 + ki * 2 + (k & 1)) * (SLOT >> 4) + (m - ki * 3) * 192, k ? 1 : m);
            wgmma_commit();
            wgmma_wait<0>();
          }
        }
        acc_fence(acc);
        TSE(1);
        asm volatile("bar.sync %0, 128;\n" ::"r"(1 + wg) : "memory");
#pragma unroll
        for (int jp = 0; jp < 6; jp++) stage16<4096>(acc, jp, win + warp * 1024 + (lane & 15) * 64 + ((((lane >> 4) ^ (lane >> 1)) & 3) << 4));
        proxy_fence();
        asm volatile("bar.sync %0, 128;\n" ::"r"(1 + wg) : "memory");
        if (lead) {
          tma_store(&tm.gout, win, tx, ty);
          asm volatile("cp.async.bulk.commit_group;\ncp.async.bulk.wait_group.read 0;\n" ::: "memory");
          TSE(2);
        }
      }
    }
  } else if (wid < 12) {
    asm volatile("setmaxnreg.dec.sync.aligned.u32 32;\n");
    const int tid = thread_id(), lane = tid & 31;

    const bool one = elect_one();
    if (one && cta < NI) {
#pragma unroll
      for (int i = 0; i < 4; i++) mbar_init(bars + (B_G + (wid - 8) * 4 + i) * 8, 1);
      asm volatile("fence.mbarrier_init.release.cluster;\n" ::: "memory");
    }
    if (one && cta >= NI) {
#pragma unroll
      for (int i = 0; i < 7; i++) mbar_init(bars + (B_WF + 8 + (wid - 8) * 7 + i) * 8, 1);
      if (wid == 8) mbar_init(bars + B_WF * 8, 12);
      mbar_init(bars + (B_UR + wid - 8) * 8, 1);
      asm volatile("fence.mbarrier_init.release.cluster;\n" ::: "memory");
    }
    asm volatile("bar.arrive 3, 256;\n" ::: "memory");
    asm volatile("bar.sync 0, 512;\n" ::: "memory");
    if (cta >= NI) {
      mbar_wait(bars + (B_WF + 1) * 8);
#pragma unroll 1
      for (int t = tid; t < 1152; t += 384) {
        uint32_t g[3][4];
        const uint32_t src = sbase + u_src(t);
#pragma unroll
        for (int k = 0; k < 3; k++) lds128(g[k], src + k * 2 * SLOT);
        u_math16(g, sbase + u_dst(t));
      }
      proxy_fence();
      __syncwarp();
      arrive_if(one ? bars + B_WF * 8 : 0u);
      uint32_t a[4], d[6][2];
#pragma unroll
      for (int j = 0; j < 4; j++) a[j] = swz(sbase + SM_V + j * PLANE + ((tid & 127) >> 3) * 64, lane >> 1) + (lane & 1) * 8;
      const bool bot = y0 == 216;
      uint32_t off = 0;
#pragma unroll 1
      for (int u = 0; u < 6; u++) {
        const uint32_t a5 = bot && ((u ^ ry) & 1) ? a[0] : a[1], o34 = u & 1 ? 0 : 4 * PLANE;
        mbar_wait(bars + (B_XF + u) * 8);
#pragma unroll 1
        for (int i = 0; i < ((u & 3) == (wid & 3) ? 3 : 2); i += i ? 1 : 1 + (u & 1)) {
          const uint32_t h = off + (i < 2 ? i * 1024 : 4096 - (wid & 2) * 256);
          v_load(d, a, a5, i == 2 && (lane & 16 || (x0 == 160 && lane >= 8)) ? h - (lane >> 3) * 64 : h);
          v_store(d, a, 4 * PLANE - o34, o34, h, i == 2 && lane >= 16 ? -1 : 0);
        }
        proxy_fence();
        __syncwarp();
        arrive_if(one ? bars + (B_XR + u) * 8 : 0u);
        off += UNIT + ((u ^ wid) & 1 ? -256 : 256);
      }
    }
  } else {
    asm volatile("setmaxnreg.dec.sync.aligned.u32 32;\n");
    const int tid = thread_id(), lane = tid & 31;
    const bool one = elect_one();
    if (wid != 12) {
      if (one) {
        if (cta >= NI) {
          if (wid == 13) {
#pragma unroll
            for (int i = 0; i < 6; i++) mbar_init(bars + (B_XR + i) * 8, 8);
          } else if (wid == 15) {
#pragma unroll
            for (int i = 2; i < 6; i++) mbar_init(bars + (B_XF + i) * 8, 1);
          }
        } else {
#pragma unroll
          for (int i = 0; i < 3; i++) mbar_init(bars + (B_WF + 1 + (wid - 13) * 3 + i) * 8, 1);
          if (wid < 15) mbar_init(bars + (wid == 13 ? B_WE : B_WF) * 8, wid == 13 ? 8 : 1);
          mbar_init(bars + (B_XF + wid - 13) * 8, 1);
        }
        if (wid == 14) {
#pragma unroll
          for (int i = 0; i < 8; i++) mbar_init(bars + (B_ST + i) * 8, 4);
#pragma unroll
          for (int i = B_OF; i <= B_OK; i++) mbar_init(bars + i * 8, i != B_OS ? 1 : cta < NI ? 8 : 2);
          if (cta >= NI) mbar_init(bars + B_CR * 8, 1);
          sts32(bars + O_CNT, 0);
        }
        asm volatile("fence.mbarrier_init.release.cluster;\n" ::: "memory");
      }
      asm volatile("bar.arrive 3, 256;\n" ::: "memory");
      asm volatile("bar.sync 0, 512;\n" ::: "memory");
      if (cta >= 48 && cta < NI) {
        if (wid == 15 && one) asm volatile("red.relaxed.gpu.global.add.u32 [%0], 1;\n" ::"l"(tm.scr->ready + 6) : "memory");
      } else {
        uint32_t epoch = 0;
        if (cta >= NI && wid < 15) {
          const uint32_t lim = (pack2((float)max(y0, 34) - 1.5f, (float)max(x0, 34) - 1.5f) & 0x7f807f80u) - 0x04000400u;
          uint32_t big = 0;
          mbar_wait(bars + B_OF * 8);
#pragma unroll 1
          for (int i0 = 0; i0 < 18; i0 += 6) {
            uint32_t v[6][4];
#pragma unroll
            for (int i = 0; i < 6; i++) lds128(v[i], sbase + SM_OFF + (tid - 416) * 16 + (i0 + i) * 1024);
            __nv_bfloat162 mx = as_bf2(0u), mn = as_bf2(0u);
#pragma unroll
            for (int i = 0; i < 6 * 2; i++) {
              mx = __hmax2_nan(__hmax2_nan(mx, as_bf2(v[i >> 1][(i & 1) * 2])), as_bf2(v[i >> 1][(i & 1) * 2 + 1]));
              mn = __hmin2_nan(__hmin2_nan(mn, as_bf2(v[i >> 1][(i & 1) * 2])), as_bf2(v[i >> 1][(i & 1) * 2 + 1]));
            }
            big |= __hblt2(__hmax2_nan(mx, __hneg2(mn)), as_bf2(lim)) ? 0u : 1u << i0;
          }
          __syncwarp();
          arrive_if(one ? bars + B_OS * 8 : 0u);
          if (wid == 13) {
            mbar_wait(bars + B_OS * 8);
            mbar_wait(bars + (B_WF + 8) * 8);
            if (one) {
              mbar_expect_tx(bars + (B_XF + 5) * 8, UNIT);
              tma_load_3d(sbase + SM_V + 5 * UNIT, &tm.x, bars + (B_XF + 5) * 8, 64, x0 - 1, y0 + (~ry & 1) * 4 - 1);
            }
          }
#pragma unroll 1
          for (uint32_t who; (who = __ballot_sync(0xffffffffu, big)) != 0;) {
            const int src = __ffs(who) - 1;
            const uint32_t b = __reduce_or_sync(0xffffffffu, lane == src ? big : 0u);
            if (lane == src) big &= big - 1;
            const uint32_t wi = ((wid - 13) * 32 + src + (__ffs(b) - 1 + (lane >> 2)) * 64) * 4 + (lane & 3), id = (wi * 7282) >> 16, tap = wi - id * 9;
            const int ki = (tap * 11) >> 5, h = y0 + (id >> 6), w = x0 + (id & 63);
            mbar_wait(bars + B_EP * 8);
            epoch = lds32(bars + O_EPO);
            if (lds32(bars + O_CNT) > MAXEX) big = 0;
            if (lane < 24 && h >= 34 && w >= 34) {
              const uint32_t gp = pack2((float)(h + ki - 1), (float)(w + (int)tap - ki * 3 - 1));
              const uint32_t pos = clip2(hadd2(gp, __ldg(offs + (h * IW + w) * 9 + tap)));
              if (pos != hmin2(gp, 0x435f435fu)) {
                const uint32_t i = count_up(bars + O_CNT);
                if (i < MAXEX)
                  sts32(bars + O_LST + i * 4, id | (request(tm.scr, min(atomicAdd(tm.scr->ready + 8 + ((epoch >> 7) & 1), 1u) + EARLY, QUEUE), pos, h, w, tap) << 16));
              }
            }
            __syncwarp();
          }
          if (wid == 14) asm volatile("bar.arrive 7, 64;\n" ::: "memory");
        }
        if (wid == 13) {
          uint32_t m[2] = {}, cnt = 0;
          mbar_wait(bars + B_EP * 8);
          epoch = lds32(bars + O_EPO);
          if (cta >= NI ? x0 == 32 || y0 == 32 : g0 == 32) {
#pragma unroll 1
            for (uint32_t spin = 0;; spin++) {
              ld_pair(m, tm.scr->mail[cta] + min(lane, MAXEX));
              const uint32_t have = __ballot_sync(0xffffffffu, m[1] == epoch);
              cnt = __reduce_max_sync(0xffffffffu, lane == MAXEX ? m[0] : 0u);
              if ((have >> MAXEX) && (cnt > MAXEX || !(~have & ((1u << cnt) - 1)))) break;
              if (spin > (1u << 22)) __trap();
            }
          }
          if (cta >= NI) asm volatile("bar.sync 7, 64;\n" ::: "memory");
          else mbar_wait(bars + B_OS * 8);
          if (one) asm volatile("red.relaxed.gpu.global.add.u32 [%0], 1;\n" ::"l"(tm.scr->ready + 6) : "memory");
          const uint32_t own = lds32(bars + O_CNT);
          if (own && lane >= cnt) m[0] = lds32(bars + O_LST + ((lane - cnt) & 15) * 4);
          cnt += own;
          if (cnt > MAXEX || __any_sync(0xffffffffu, lane < cnt && m[0] >> 16 == QUEUE)) cnt = FAILED;
          const uint32_t id = lane < cnt ? m[0] & 511 : 512;
          const uint32_t rows = cnt == FAILED ? FAILED : __reduce_or_sync(0xffffffffu, lane < cnt ? 1u << (id >> (cta < NI ? 7 : 6)) : 0u);
          __syncwarp();
          if (lane < 16) sts32(bars + O_LST + lane * 4, id);
          if (one) sts32(bars + O_VER, rows);
          __syncwarp();
          arrive_if(one ? bars + B_OK * 8 : 0u);
          TSE(0);
          if (cnt) {
            const uint32_t z[4] = {};
#pragma unroll
            for (int k = 0; k < 6; k++) sts128(bars + O_COR + k * 512 + lane * 16, z);
            __syncwarp();
          }
#pragma unroll 1
          for (uint32_t got = 0; got < cnt && cnt != FAILED; got += 4) {
            const uint32_t i = min(got + (lane >> 3), cnt - 1);
            const uint2* r = tm.scr->res[__shfl_sync(0xffffffffu, m[0], i) >> 16] + (lane & 7);
            uint32_t v[12];
#pragma unroll 1
            for (uint32_t spin = 0;; spin++) {
              uint32_t miss = 0;
#pragma unroll
              for (int k = 0; k < 6; k++) ld_pair(v + k * 2, r + k * 8);
#pragma unroll
              for (int k = 0; k < 6; k++) miss |= v[k * 2 + 1] ^ epoch;
              if (__all_sync(0xffffffffu, !miss)) break;
              if (spin > (1u << 22)) __trap();
            }
#pragma unroll
            for (int k = 0; k < 6; k++)
              sts32(swz(bars + O_COR + (k >> 1) * 1024 + i * 64, (k & 1) * 2 + ((lane >> 2) & 1)) + (lane & 3) * 4, v[k * 2]);
          }
          proxy_fence();
          __syncwarp();
          arrive_if(one ? bars + B_CR * 8 : 0u);
#pragma unroll 1
          for (int i = cnt && cnt != FAILED ? -1 : 4; i < 4; i++) {
            const int t = (i >> 1) & 1, r = i & 1, row = cta < NI ? i : ((t ^ ry) & 1) * 4 + 2 - r;
            if (i >= 0 && !((rows >> row) & 1)) continue;
            const uint32_t base = cta < NI ? sbase + (i & 1) * 3 * SLOT : sbase + SM_X + (2 + r * 2) * UNIT + t * 21504;
            const uint32_t pitch = cta < NI ? 8192 : 4096;
            patch(bars + (i < 0 ? B_OK : B_ST + (cta < NI ? i : t) * 4) * 8, i < 0 ? lane ? 512 : 0 : id - (row << (cta < NI ? 7 : 6)),
                  cta < NI ? 128 : 64, base, pitch, bars, i < 0 ? 12 : lane);
            if (one && i >= 0) {
              if (cta < NI) {
                tma_store(&tm.bout[band], base, g0, i * 16);
              } else {
#pragma unroll
                for (int k = 0; k < 3; k++) tma_store3(&tm.out, base + k * pitch, k * 32, x0, y0 + row);
              }
            }
          }
          if (one) asm volatile("cp.async.bulk.commit_group;\ncp.async.bulk.wait_group.read 0;\n" ::: "memory");
          TSE(2);
        } else {
          if (wid == 15) {
            auto poll = [&]() {
              uint32_t v;
              asm volatile("ld.acquire.gpu.global.u32 %0, [%1];\n" : "=r"(v) : "l"(tm.scr->ready + min(lane, 6)) : "memory");
              return v;
            };
            const uint32_t epoch = (__reduce_max_sync(0xffffffffu, lane == 6 ? poll() : 0u) & ~127u) + 128;
            if (one) sts32(bars + O_EPO, epoch);
            arrive_if(one ? bars + B_EP * 8 : 0u);
            if (cta >= NI) {
              uint32_t seen = 0;
              wait_until(tstart, POLLT);
#pragma unroll 1
              for (uint32_t spin = 0; seen != 7; spin++) {
                const uint32_t now = __ballot_sync(0xffffffffu, poll() == epoch) & ~seen & 7;
                if (now) {
                  asm volatile("fence.proxy.async.global;\n" ::: "memory");
                  arrive_if((now >> lane) & 1 ? bars + (B_UR + lane) * 8 : 0u);
                  seen |= now;
                }
                if (spin > (1u << 22)) __trap();
              }
            }
          }
          asm volatile("prefetch.tensormap [%0];\n" ::"l"(reinterpret_cast<uint64_t>(cta < NI ? &tm.bout[band] : &tm.out)) : "memory");
          const int t = wid & 1;
          mbar_wait(bars + B_OK * 8);
          const int r0 = cta < NI ? t : ((t ^ ry) & 1) * 4;
          uint32_t skip = __shfl_sync(0xffffffffu, lds32(bars + O_VER), 0);
          skip = (skip == FAILED || cta < NI ? skip : skip & 0x66) >> r0;
          if (cta < NI) {
            mbar_wait(bars + (B_ST + t * 4) * 8);
            if (one && !(skip & 1)) tma_store(&tm.bout[band], sbase + t * 3 * SLOT, g0, t * 16);
          } else {
#pragma unroll
            for (int r = 0; r < 4; r++) {
              const uint32_t base = r < 2 ? sbase + SM_X + (2 + r * 2) * UNIT + t * 21504 : sbase + SM_V + t * (UNIT + 4 * PLANE) + (r - 2) * PLANE;
              if (r != 1) mbar_wait(bars + (B_ST + t * 4 + max(r - 1, 0)) * 8);
              if (r == 1) mbar_wait(bars + (B_UR + 3) * 8);
              if (!((skip >> ((2 - r) & 3)) & 1)) {
#pragma unroll
                for (int k = 0; k < 3; k++)
                  if (one) tma_store3(&tm.out, base + k * (r < 2 ? 4096 : 2 * UNIT), k * 32, x0, y0 + r0 + ((2 - r) & 3));
              }
            }
          }
          if (one) asm volatile("cp.async.bulk.commit_group;\ncp.async.bulk.wait_group.read 0;\n" ::: "memory");
          TSE(2);
        }
      }
    } else if (cta < NI) {
        auto load_x = [&](int s) {
          mbar_expect_tx(bars + (B_XF + s) * 8, YSLICE);
          tma_load_3d(sbase + SM_YX + s * YSLICE, &tm.bx[band], bars + (B_XF + s) * 8, s * 32, g0 - 1, -2);
        };
        auto load_w = [&](int p) {
          const int s = (p * 11) >> 5, b = p - s * 3;
          mbar_expect_tx(bars + (B_WF + p) * 8, 2 * SLOT);
#pragma unroll
          for (int h = 0; h < 2; h++)
            tma_load_5d(sbase + (p * 2 + h) * SLOT, &tm.bw[band], bars + (B_WF + p) * 8, s * 32 + h * 16, band ? 0 : b, band ? b : 0);
        };
        asm volatile("bar.arrive 0, 512;\n" ::: "memory");
        asm volatile("bar.sync 3, 256;\n" ::: "memory");
        if (one && cta >= 48) {
#pragma unroll 1
          for (int sl = 0; sl < 3; sl++) {
            wait_until(tstart, CSLEEP + sl * GDT);
#pragma unroll
            for (int wg = 0; wg < 2; wg++) {
              mbar_expect_tx(bars + (B_G + 9 + wg * 3 + sl) * 8, GSLICE);
              tma_load_3d(sbase + SM_GX + (wg * 3 + sl) * GSLICE, &tm.gx, bars + (B_G + 9 + wg * 3 + sl) * 8, sl * 32,
                          (cta & 2) * 4 + ((cta >> 2 ^ wg) & 1) * 16 - 2, (cta & 1) * 8 + wg * 16 - 2);
            }
#pragma unroll 1
            for (int i = 0; i < 6; i++) {
              if (!(i & 1)) mbar_expect_tx(bars + (B_G + sl * 3 + (i >> 1)) * 8, 2 * SLOT);
              tma_load_5d(sbase + (sl * 6 + i) * SLOT, &tm.bw[1], bars + (B_G + sl * 3 + (i >> 1)) * 8, sl * 32 + (i & 1) * 16, 0, i >> 1);
            }
          }
        }
        if (one && cta < 48) {
          arrive_if(bars + (B_WF + 9) * 8);
#pragma unroll 1
          for (int p = 0; p < 9; p++) {
            wait_until(tstart, p > 4 ? YWT + 3 * YWDT + (p - 4) * YWD2 : p ? YWT + (p - 1) * YWDT : BSLEEP);
            if (p == 0 || p == 3 || p == 6) load_x(p >> 1 & 1 ? (p >> 2) + 1 : 0);
            if (p == 8) mbar_wait(bars + B_WE * 8);
            load_w(p);
          }
        }
    } else {
        auto load_x = [&](int u) {
          mbar_expect_tx(bars + (B_XF + u) * 8, UNIT);
          tma_load_3d(sbase + SM_V + u * UNIT, &tm.x, bars + (B_XF + u) * 8, (u >> 1) * 32, x0 - 1, y0 + ((u ^ ry) & 1) * 4 - 1);
        };
        asm volatile("bar.sync 3, 256;\n" ::: "memory");
        if (lane < 28) mbar_expect_tx(bars + (B_WF + 8 + lane) * 8, lane == 16 ? 3 * SLOT : lane == 17 || lane == 18 ? 0 : SLOT);
        if (smem_u32(smem) != sbase) __trap();
#pragma unroll 1
        for (int xu = 2; xu <= 3; xu++) {
          wait_until(tstart, xu == 2 ? XT2 : XT3);
          if (xu == 3) mbar_wait(bars + B_WF * 8);
          if (one) load_x(xu);
          if (xu == 3 && one) {
            mbar_expect_tx(bars + B_OF * 8, 2 * SLOT);
            tma_load_3d(sbase + SM_OFF, &tm.off, bars + B_OF * 8, 0, x0 * 9 / 32, y0);
          }
        }
        const uint4* src = tm.scr->u;
        uint32_t fb = bars + (B_WF + 8) * 8;
#pragma unroll 1
        for (int q = 0; q < 6; q++) {
          mbar_wait(bars + (B_UR + (q >> 1)) * 8);
          if (q == 4) {
            if (one) bulk_load<3 * SLOT>(sbase + SM_X, src, fb);
            if (one) bulk_load<SLOT>(sbase + SM_X + 2 * UNIT + 12288, src + 3 * 576, fb + 24);
            src += 4 * 576;
            fb += 32;
          }
          const uint32_t dst = sbase + SM_W + (q & 1) * 4 * SLOT, id = 8 + (q & 1) * 4;
#pragma unroll
          for (int k = 0; k < 4; k++) {
            asm volatile("bar.sync %0, 96;\n" ::"r"(id + k) : "memory");
            if (one) bulk_load<SLOT>(dst + k * SLOT, src + k * 576, fb + k * 8);
            if (k == 3 && q == 5 && one) arrive_if(bars + (B_UR + 3) * 8);
          }
          if (q == 1 && one) load_x(4);
          src += 4 * 576;
          fb += 32;
        }
    }
  }
}

typedef CUresult (*EncodeTiledFn)(CUtensorMap*, CUtensorMapDataType, cuuint32_t, void*, const cuuint64_t*,
                                  const cuuint64_t*, const cuuint32_t*, const cuuint32_t*, CUtensorMapInterleave,
                                  CUtensorMapSwizzle, CUtensorMapL2promotion, CUtensorMapFloatOOBfill);

}

extern "C" void kernel_launch(void* const* d_in, const int* in_sizes, int n_in, void* d_out, int out_size) {
  static EncodeTiledFn encode = nullptr;
  static Scratch* scratch = nullptr;
  if (!encode) {
    void* fn = nullptr;
    cudaDriverEntryPointQueryResult qres;
    cudaGetDriverEntryPoint("cuTensorMapEncodeTiled", &fn, cudaEnableDefault, &qres);
    encode = (EncodeTiledFn)fn;
    cudaGetSymbolAddress((void**)&scratch, g_scratch);
    cudaFuncSetAttribute(dcn_kernel, cudaFuncAttributeMaxDynamicSharedMemorySize, SMEM_BYTES);
  }
  uint32_t* tsp = nullptr;
  Maps tm;
  tm.scr = scratch;
  auto make = [&](CUtensorMap* m, void* p, int rank, const cuuint64_t* dims, const cuuint64_t* strides, const cuuint32_t* box, bool swizzle) {
    const cuuint32_t es[5] = {1, 1, 1, 1, 1};
    encode(m, CU_TENSOR_MAP_DATA_TYPE_BFLOAT16, rank, p, dims, strides, box, es, CU_TENSOR_MAP_INTERLEAVE_NONE,
           swizzle ? CU_TENSOR_MAP_SWIZZLE_64B : CU_TENSOR_MAP_SWIZZLE_NONE, CU_TENSOR_MAP_L2_PROMOTION_NONE,
           CU_TENSOR_MAP_FLOAT_OOB_FILL_NONE);
  };
  const cuuint64_t PX = IC * 2, ROW = IW * IC * 2, TAP = IC * IC * 2;
  for (int t = 0; t < 2; t++) {
    const cuuint64_t dims[3] = {IC, IW, IH}, odims[4] = {32, IW, IH, 3}, strides[3] = {t ? ROW : PX, t ? PX : ROW, 64};
    const cuuint32_t xb[3] = {32, 66, 6}, ob[3] = {32, 64, 1}, bxb[3] = {32, 10, 36}, bob[4] = {32, 8, 16, 3};
    if (!t) make(&tm.x, d_in[0], 3, dims, strides, xb, true);
    if (!t) make(&tm.out, d_out, 3, dims, strides, ob, true);
    const cuuint32_t gxb[3] = {32, 12, 12}, gob[4] = {32, 8, 8, 3};
    if (!t) make(&tm.gx, d_in[0], 3, dims, strides, gxb, true);
    if (!t) make(&tm.gout, d_out, 4, odims, strides, gob, true);
    make(&tm.bx[t], d_in[0], 3, dims, strides, bxb, true);
    make(&tm.bout[t], d_out, 4, odims, strides, bob, true);
    const cuuint64_t wdims[5] = {32, IC, 3, 3, 3}, wstrides[4] = {PX, 64, TAP, 3 * TAP};
    const cuuint32_t wb[5] = {32, 16, 3, t ? 3u : 1u, t ? 1u : 3u};
    make(&tm.bw[t], d_in[2], 5, wdims, wstrides, wb, true);
  }
  {
    const cuuint64_t dims[3] = {64, 144, 9}, strides[2] = {128, TAP};
    const cuuint32_t box[3] = {64, 48, 9};
    make(&tm.w, d_in[2], 3, dims, strides, box, false);
    const cuuint64_t cdims[4] = {64, 144, 3, 3}, cstrides[3] = {128, TAP, 3 * TAP};
    const cuuint32_t cbox[4] = {64, 24, 1, 3};
    make(&tm.wc, d_in[2], 4, cdims, cstrides, cbox, false);
    const cuuint64_t odims[3] = {64, 63, IH}, ostrides[2] = {128, IW * 36};
    const cuuint32_t obox[3] = {64, 18, 8};
    make(&tm.off, d_in[1], 3, odims, ostrides, obox, false);
    const cuuint32_t cb[3] = {64, 1, IH};
    make(&tm.col, d_in[1], 3, odims, ostrides, cb, false);
  }
  dcn_kernel<<<GRID, NTHREADS, SMEM_BYTES>>>((const uint4*)d_in[0], (const uint32_t*)d_in[1], tsp, 0u, tm);
}
```
